```python
import torch

def _softmax(x, axis=-1):
    return torch.softmax(x, dim=axis)
def _gelu(x):
    return torch.nn.functional.gelu(x, approximate="tanh")
def _silu(x):
    return torch.nn.functional.silu(x)
def _sigmoid(x):
    return torch.sigmoid(x)
def _layernorm(x, axis=-1, eps=1e-5):
    m = x.mean(dim=axis, keepdim=True)
    v = x.var(dim=axis, keepdim=True, unbiased=False)
    return (x - m) / torch.sqrt(v + eps)
def _scatter_add(tgt, idx, src, axis=0):
    return tgt.clone().index_add_(axis, idx, src)
def _segment_sum(src, seg, n):
    out = torch.zeros((n,) + src.shape[1:], dtype=src.dtype)
    return out.index_add_(0, seg, src)
def _pad(x, pw):
    flat = tuple(v for pair in reversed(pw) for v in pair)
    return torch.nn.functional.pad(x, flat)

kernel_name = 'standalone__low_rank_proj_linformer__prompt'

def setup_inputs():

    _w = (lambda a: (lambda t: t.to(torch.bfloat16) if t.is_floating_point() else t)(torch.as_tensor(a)))
    B, H, Sq, Skv, Dh, R = 1, 32, 2048, 2048, 128, 8
    return {
        "q": _w((lambda *s: torch.randn(*s, dtype=torch.bfloat16) * 0.8)(B, H, Sq, Dh)),
        "k": _w((lambda *s: torch.randn(*s, dtype=torch.bfloat16) * 0.8)(B, H, Skv, Dh)),
        "v": _w((lambda *s: torch.randn(*s, dtype=torch.bfloat16) * 0.05)(B, H, Skv, Dh)),
        "e_proj": _w((lambda *s: torch.randn(*s, dtype=torch.bfloat16) * 0.8)(R, Skv) * (Skv ** -0.5)),
        "f_proj": _w((lambda *s: torch.randn(*s, dtype=torch.bfloat16) * 0.05)(R, Skv) * (Skv ** -0.5)),
    }

def reference(q, k, v, e_proj, f_proj):
    B, H, Sq, Dh = q.shape
    kp = torch.einsum("rn,bhnd->bhrd", e_proj, k)
    vp = torch.einsum("rn,bhnd->bhrd", f_proj, v)
    scores = torch.einsum("bhqd,bhrd->bhqr", q, kp) * (Dh ** -0.5)
    p = _softmax(scores, axis=-1)
    o = torch.einsum("bhqr,bhrd->bhqd", p, vp)
    return o
```

```cpp
#include <cuda_runtime.h>
#include <cuda_bf16.h>
#include <cuda.h>
#include <stdint.h>

namespace {

typedef __nv_bfloat16 bf16;

constexpr int DH = 128;
constexpr int CL = 6;
constexpr int NT = 32;
constexpr int TILE = 16384;
constexpr int STAGES = 10;
constexpr int NQW = 8;
constexpr int NPRE = 3;
constexpr int NTHR = (7 + NQW) * 32;
constexpr int SMEM_BYTES = STAGES * TILE + 11 * 1024 + 12 * 1024 + 8192 + 2048;

constexpr unsigned mkmask(const char* s) {
    unsigned m = 0;
    for (int i = 0; i < 32; i++) if (s[i] == 'Q') m |= 1u << i;
    return m;
}
constexpr unsigned QMASK0 = mkmask("KKKKKKKKKKKKQKKQKKQKKQKKQKKQQQQQ");
constexpr unsigned QMASK1 = mkmask("KKKKKKKKKKKKQKQKQKQKQKQKQKKQQQQQ");
constexpr int LAST_KV = 26;

__device__ __forceinline__ uint32_t smem_u32(const void* p) { return (uint32_t)__cvta_generic_to_shared(p); }
__device__ __forceinline__ void mbar_init(uint32_t bar, uint32_t cnt) { asm volatile("mbarrier.init.shared::cta.b64 [%0], %1;" :: "r"(bar), "r"(cnt) : "memory"); }
__device__ __forceinline__ void mbar_expect_tx(uint32_t bar, uint32_t bytes) { asm volatile("mbarrier.arrive.expect_tx.shared::cta.b64 _, [%0], %1;" :: "r"(bar), "r"(bytes) : "memory"); }
__device__ __forceinline__ void mbar_arrive(uint32_t bar) { asm volatile("mbarrier.arrive.shared::cta.b64 _, [%0];" :: "r"(bar) : "memory"); }
__device__ __forceinline__ void mbar_wait(uint32_t bar, uint32_t parity) {
    uint32_t done; int it = 0;
    do {
        asm volatile("{\n.reg .pred p;\nmbarrier.try_wait.parity.shared::cta.b64 p, [%1], %2;\nselp.u32 %0, 1, 0, p;\n}" : "=r"(done) : "r"(bar), "r"(parity) : "memory");
        if (++it > (1 << 22)) __trap();
    } while (!done);
}
__device__ __forceinline__ void mbar_wait_cluster(uint32_t bar) {
    uint32_t done; int it = 0;
    do {
        asm volatile("{\n.reg .pred p;\nmbarrier.try_wait.parity.acquire.cluster.shared::cta.b64 p, [%1], 0;\nselp.u32 %0, 1, 0, p;\n}" : "=r"(done) : "r"(bar) : "memory");
        if (++it > (1 << 22)) __trap();
    } while (!done);
}
__device__ __forceinline__ void tma4(uint32_t dst, const CUtensorMap* m, int grp, uint32_t bar, uint64_t pol) {
    asm volatile("cp.async.bulk.tensor.4d.shared::cluster.global.mbarrier::complete_tx::bytes.L2::cache_hint [%0], [%1, {%3, %3, %3, %4}], [%2], %5;"
                 :: "r"(dst), "l"(m), "r"(bar), "r"(0), "r"(grp), "l"(pol) : "memory");
}
__device__ __forceinline__ void tma3(uint32_t dst, const CUtensorMap* m, int blk, uint32_t bar) {
    asm volatile("cp.async.bulk.tensor.3d.shared::cluster.global.mbarrier::complete_tx::bytes [%0], [%1, {%3, %3, %4}], [%2];"
                 :: "r"(dst), "l"(m), "r"(bar), "r"(0), "r"(blk) : "memory");
}
__device__ __forceinline__ void ldsm4(uint32_t a, uint32_t& r0, uint32_t& r1, uint32_t& r2, uint32_t& r3) {
    asm volatile("ldmatrix.sync.aligned.m8n8.x4.shared.b16 {%0,%1,%2,%3}, [%4];" : "=r"(r0), "=r"(r1), "=r"(r2), "=r"(r3) : "r"(a) : "memory");
}
__device__ __forceinline__ void ldsm4t(uint32_t a, uint32_t& r0, uint32_t& r1, uint32_t& r2, uint32_t& r3) {
    asm volatile("ldmatrix.sync.aligned.m8n8.x4.trans.shared.b16 {%0,%1,%2,%3}, [%4];" : "=r"(r0), "=r"(r1), "=r"(r2), "=r"(r3) : "r"(a) : "memory");
}
__device__ __forceinline__ void mma16816(float* c, uint32_t a0, uint32_t a1, uint32_t a2, uint32_t a3, uint32_t b0, uint32_t b1) {
    asm volatile("mma.sync.aligned.m16n8k16.row.col.f32.bf16.bf16.f32 {%0,%1,%2,%3}, {%4,%5,%6,%7}, {%8,%9}, {%0,%1,%2,%3};"
                 : "+f"(c[0]), "+f"(c[1]), "+f"(c[2]), "+f"(c[3]) : "r"(a0), "r"(a1), "r"(a2), "r"(a3), "r"(b0), "r"(b1));
}
__device__ __forceinline__ void mma1688z(float* c, uint32_t a0, uint32_t a1, uint32_t b0) {
    asm volatile("mma.sync.aligned.m16n8k8.row.col.f32.bf16.bf16.f32 {%0,%1,%2,%3}, {%4,%5}, {%6}, {%7,%7,%7,%7};"
                 : "=f"(c[0]), "=f"(c[1]), "=f"(c[2]), "=f"(c[3]) : "r"(a0), "r"(a1), "r"(b0), "f"(0.f));
}
__device__ __forceinline__ uint32_t pack2(float lo, float hi) { uint32_t r; asm("cvt.rn.bf16x2.f32 %0, %1, %2;" : "=r"(r) : "f"(hi), "f"(lo)); return r; }
__device__ __forceinline__ float ex2(float x) { float y; asm("ex2.approx.ftz.f32 %0, %1;" : "=f"(y) : "f"(x)); return y; }
__device__ __forceinline__ float rcpa(float x) { float y; asm("rcp.approx.ftz.f32 %0, %1;" : "=f"(y) : "f"(x)); return y; }
__device__ __forceinline__ uint32_t mapa(uint32_t a, int r) { uint32_t o; asm("mapa.shared::cluster.u32 %0, %1, %2;" : "=r"(o) : "r"(a), "r"(r)); return o; }
__device__ __forceinline__ void st_async4(uint32_t a, uint32_t x, uint32_t y, uint32_t z, uint32_t w, uint32_t b) {
    asm volatile("st.async.weak.shared::cluster.mbarrier::complete_tx::bytes.v4.b32 [%0], {%1,%2,%3,%4}, [%5];" :: "r"(a), "r"(x), "r"(y), "r"(z), "r"(w), "r"(b) : "memory");
}
__device__ __forceinline__ float4 lds4(uint32_t a) { float4 x; asm volatile("ld.shared.v4.f32 {%0,%1,%2,%3}, [%4];" : "=f"(x.x), "=f"(x.y), "=f"(x.z), "=f"(x.w) : "r"(a) : "memory"); return x; }
__device__ __forceinline__ float2 lds2(uint32_t a) { float2 x; asm volatile("ld.shared.v2.f32 {%0,%1}, [%2];" : "=f"(x.x), "=f"(x.y) : "r"(a) : "memory"); return x; }
__device__ __forceinline__ uint4 ldsu4(uint32_t a) { uint4 x; asm volatile("ld.shared.v4.u32 {%0,%1,%2,%3}, [%4];" : "=r"(x.x), "=r"(x.y), "=r"(x.z), "=r"(x.w) : "r"(a) : "memory"); return x; }

__global__ void __cluster_dims__(CL, 1, 1) __launch_bounds__(NTHR, 1)
linformer_kernel(const __grid_constant__ CUtensorMap mk, const __grid_constant__ CUtensorMap mv,
                 const __grid_constant__ CUtensorMap me, const __grid_constant__ CUtensorMap mf,
                 const __grid_constant__ CUtensorMap mq, bf16* __restrict__ out) {
    extern __shared__ __align__(1024) char smem_raw[];
    const uint32_t sbase = smem_u32(smem_raw);
    const uint32_t sproj = sbase + STAGES * TILE, srecv = sproj + 11 * 1024, sfrag = srecv + 12 * 1024;
    const uint32_t bfull = sfrag + 8192, bempty = bfull + 8 * NT * 4, bproj = bempty + 8 * STAGES, bx = bproj + 8, bfr = bx + 32;
    const int tid = threadIdx.x, warp = tid >> 5, lane = tid & 31;
    uint32_t rank, cl;
    asm("mov.u32 %0, %%cluster_ctarank;" : "=r"(rank));
    asm("mov.u32 %0, %%clusterid.x;" : "=r"(cl));
    const int isv = rank >= 3, r3 = rank - 3 * isv, rc = r3 == 2;
    const unsigned qm = rc ? QMASK1 : QMASK0;
    if (warp == 0) {
        const CUtensorMap* mkv = isv ? &mv : &mk;
        const int kvc = cl * 512 + r3 * 88;
        uint64_t pol;
        asm volatile("createpolicy.fractional.L2::evict_first.b64 %0, 1.0;" : "=l"(pol));
        if (lane == 0) {
            #pragma unroll
            for (int t = 0; t < NPRE; t++) mbar_init(bfull + 32 * t, 1);
            mbar_init(bproj, 1);
            asm volatile("fence.proxy.async.shared::cta;" ::: "memory");
            #pragma unroll
            for (int t = 0; t < NPRE; t++) {
                mbar_expect_tx(bfull + 32 * t, TILE);
                tma4(sbase + t * TILE, mkv, kvc + t * 8, bfull + 32 * t, pol);
                if (t == 0) { mbar_expect_tx(bproj, 11 * 1024); tma3(sproj, isv ? &mf : &me, r3 * 11, bproj); }
            }
            asm volatile("prefetch.tensormap [%0];" :: "l"(&mq) : "memory");
        }
        __syncwarp();
        asm volatile("bar.sync 1, %0;" :: "n"(NTHR) : "memory");
        asm volatile("barrier.cluster.arrive.relaxed.aligned;" ::: "memory");
        if (lane == 0) {
            const int nkv = 11 - rc, nA = rc ? 26 : 19;
            const int qA = cl * 512 + (isv * 64 + r3 * 19) * 2, qB = cl * 512 + 256 + (isv * 64 + r3 * 21) * 2 - nA * 2;
            int ik = NPRE, iq = 0, s = NPRE; unsigned ph = 1;
            #pragma unroll 1
            for (int t = NPRE; t < NT; t++) {
                if (t >= STAGES) mbar_wait(bempty + 8 * s, ph);
                const int u = t - (t > LAST_KV ? 3 : 4);
                if (u >= 0) mbar_wait(bfull + 32 * u + (((qm >> u) & 1) ? 24 : 0), 0);
                if (!((qm >> t) & 1)) {
                    mbar_expect_tx(bfull + 32 * t, TILE);
                    tma4(sbase + s * TILE, mkv, kvc + (ik < nkv ? ik * 8 : 256 + (ik - nkv) * 8), bfull + 32 * t, pol);
                    ik++;
                } else {
                    #pragma unroll
                    for (int i = 0; i < 4; i++) {
                        mbar_expect_tx(bfull + 32 * t + 8 * i, 4096);
                        tma4(sbase + s * TILE + i * 4096, &mq, (iq < nA ? qA : qB) + 2 * iq, bfull + 32 * t + 8 * i, pol);
                        iq++;
                    }
                }
                if (++s == STAGES) { s = 0; ph ^= 1; }
            }
        }
        __syncwarp();
        asm volatile("barrier.cluster.wait.aligned;" ::: "memory");
        return;
    }
    {
        const int i = tid - 32;
        if (i < NT * 4) { if (i >= NPRE * 4) mbar_init(bfull + 8 * i, 1); }
        else if (i < NT * 4 + STAGES) mbar_init(bfull + 8 * i, 4);
        else if (i < NT * 4 + STAGES + 6) { int k = i - NT * 4 - STAGES; mbar_init(bx + 8 * k, 1); mbar_expect_tx(bx + 8 * k, k < 4 ? 3072 : 4096); }
        asm volatile("fence.proxy.async.shared::cta;" ::: "memory");
        asm volatile("fence.mbarrier_init.release.cluster;" ::: "memory");
        asm volatile("bar.sync 1, %0;" :: "n"(NTHR) : "memory");
        asm volatile("barrier.cluster.arrive.relaxed.aligned;" ::: "memory");
        asm volatile("barrier.cluster.wait.aligned;" ::: "memory");
    }
    const int g = lane >> 2, tq = lane & 3;
    const int mi = lane >> 3, li = lane & 7;
    if (warp <= 4) {
        const int w = warp - 1;
        const uint32_t aoff0 = (mi >> 1) * 2048 + (w >> 1) * 1024 + li * 128 + (((((w & 1) << 2) + (mi & 1)) ^ li) << 4);
        const uint32_t aoff1 = aoff0 ^ 32;
        const uint32_t boff0 = sproj + li * 128 + ((mi ^ li) << 4);
        const int nkv = 11 - rc;
        const int dr = isv * 3 + min(w, 2);
        const uint32_t ra = mapa(srecv + (w == 3) * 3072 + r3 * 1024 + lane * 16, dr), rb = mapa(bx + (w == 3) * 8, dr);
        unsigned km = ~qm;
        mbar_wait(bproj, 0);
        #pragma unroll 1
        for (int hg = 0; hg < 2; hg++) {
            float acc[2][2][4] = {};
            #pragma unroll 1
            for (int i = 0; i < nkv; i++) {
                const int t = __ffs(km) - 1; km &= km - 1;
                const int s = t % STAGES;
                uint32_t bb[8];
                ldsm4(boff0 + i * 1024, bb[0], bb[1], bb[2], bb[3]);
                ldsm4((boff0 ^ 64) + i * 1024, bb[4], bb[5], bb[6], bb[7]);
                mbar_wait(bfull + 32 * t, 0);
                uint32_t a[4][2][4];
                #pragma unroll
                for (int ks = 0; ks < 4; ks++) {
                    ldsm4t(sbase + s * TILE + ks * 4096 + aoff0, a[ks][0][0], a[ks][0][1], a[ks][0][2], a[ks][0][3]);
                    ldsm4t(sbase + s * TILE + ks * 4096 + aoff1, a[ks][1][0], a[ks][1][1], a[ks][1][2], a[ks][1][3]);
                }
                #pragma unroll
                for (int ks = 0; ks < 4; ks++) {
                    mma16816(acc[0][ks & 1], a[ks][0][0], a[ks][0][1], a[ks][0][2], a[ks][0][3], bb[2 * ks], bb[2 * ks + 1]);
                    mma16816(acc[1][ks & 1], a[ks][1][0], a[ks][1][1], a[ks][1][2], a[ks][1][3], bb[2 * ks], bb[2 * ks + 1]);
                }
                __syncwarp();
                if (lane == 0) mbar_arrive(bempty + 8 * s);
            }
            #pragma unroll
            for (int m = 0; m < 2; m++)
                st_async4(ra + hg * 6144 + m * 512,
                          __float_as_uint(acc[m][0][0] + acc[m][1][0]), __float_as_uint(acc[m][0][1] + acc[m][1][1]),
                          __float_as_uint(acc[m][0][2] + acc[m][1][2]), __float_as_uint(acc[m][0][3] + acc[m][1][3]), rb + hg * 16);
        }
    } else if (warp <= 6) {
        const int it = warp - 5;
        if (it == 1 && !rc) return;
        const int w = r3 + it;
        #pragma unroll 1
        for (int hg = 0; hg < 2; hg++) {
            const uint32_t src = srecv + hg * 6144 + it * 3072;
            mbar_wait_cluster(bx + hg * 16 + it * 8);
            uint32_t o[4];
            if (!isv) {
                #pragma unroll
                for (int m = 0; m < 2; m++) {
                    float4 x = lds4(src + m * 512 + lane * 16), y = lds4(src + 1024 + m * 512 + lane * 16), z = lds4(src + 2048 + m * 512 + lane * 16);
                    uint32_t k0 = pack2(x.x + y.x + z.x, x.y + y.y + z.y), k1 = pack2(x.z + y.z + z.z, x.w + y.w + z.w);
                    asm volatile("movmatrix.sync.aligned.m8n8.trans.b16 %0, %1;" : "=r"(o[2 * m]) : "r"(k0));
                    asm volatile("movmatrix.sync.aligned.m8n8.trans.b16 %0, %1;" : "=r"(o[2 * m + 1]) : "r"(k1));
                }
            } else {
                #pragma unroll
                for (int u = 0; u < 4; u++) {
                    uint32_t ad = src + (g >> 2) * 512 + ((2 * u + (g & 1)) * 4 + tq) * 16 + ((g >> 1) & 1) * 8;
                    float2 x = lds2(ad), y = lds2(ad + 1024), z = lds2(ad + 2048);
                    o[u] = pack2(x.x + y.x + z.x, x.y + y.y + z.y);
                }
            }
            const uint32_t la = sfrag + hg * 4096 + isv * 2048 + w * 512 + lane * 16, lb = bfr + hg * 8;
            #pragma unroll
            for (int rr = 0; rr < CL; rr++) {
                int r = rr + rank + 1; if (r >= CL) r -= CL;
                st_async4(mapa(la, r), o[0], o[1], o[2], o[3], mapa(lb, r));
            }
        }
    } else {
        const int w = warp - 7;
        const int rg = w & 3;
        const uint32_t qoff = sbase + (rg * 2 + (mi & 1)) * 2048 + li * 128;
        const uint32_t qx = (mi >> 1) ^ li;
        const int nA = rc ? 26 : 19, nG = rc ? 48 : 40;
        const int qA = cl * 256 + isv * 64 + r3 * 19, qB = cl * 256 + 128 + isv * 64 + r3 * 21 - nA;
        uint32_t kp[16], vp[16];
        int curg = -1;
        unsigned m = qm;
        for (int i = 0; i < (w >> 2); i++) m &= m - 1;
        #pragma unroll 1
        for (int n = w; n < nG; n += NQW) {
            const int t = __ffs(m) - 1;
            #pragma unroll
            for (int i = 0; i < NQW / 4; i++) m &= m - 1;
            const int s = t % STAGES;
            const int hg = n >= nA;
            if (hg != curg) {
                curg = hg;
                mbar_wait_cluster(bfr + 8 * hg);
                #pragma unroll
                for (int i = 0; i < 4; i++) { uint4 x = ldsu4(sfrag + hg * 4096 + i * 512 + lane * 16); kp[4 * i] = x.x; kp[4 * i + 1] = x.y; kp[4 * i + 2] = x.z; kp[4 * i + 3] = x.w; }
                #pragma unroll
                for (int i = 0; i < 4; i++) { uint4 x = ldsu4(sfrag + hg * 4096 + 2048 + i * 512 + lane * 16); vp[4 * i] = x.x; vp[4 * i + 1] = x.y; vp[4 * i + 2] = x.z; vp[4 * i + 3] = x.w; }
            }
            bf16* orow = out + ((size_t)((hg ? qB : qA) + n) * 16 + g) * DH + tq * 8;
            mbar_wait(bfull + 32 * t + 8 * rg, 0);
            float sc0[4] = {}, sc1[4] = {};
            #pragma unroll
            for (int ks = 0; ks < 8; ks++) {
                uint32_t a0, a1, a2, a3;
                ldsm4(qoff + s * TILE + (ks >> 2) * 1024 + ((qx ^ ((ks & 3) << 1)) << 4), a0, a1, a2, a3);
                mma16816((ks & 1) ? sc1 : sc0, a0, a1, a2, a3, kp[2 * ks], kp[2 * ks + 1]);
            }
            __syncwarp();
            if (lane == 0) mbar_arrive(bempty + 8 * s);
            const float c2 = 0.08838834764831845f * 1.4426950408889634f;
            float x0 = sc0[0] + sc1[0], x1 = sc0[1] + sc1[1], x2 = sc0[2] + sc1[2], x3 = sc0[3] + sc1[3];
            float m0 = fmaxf(x0, x1), m1 = fmaxf(x2, x3);
            m0 = fmaxf(m0, __shfl_xor_sync(~0u, m0, 1)); m1 = fmaxf(m1, __shfl_xor_sync(~0u, m1, 1));
            m0 = fmaxf(m0, __shfl_xor_sync(~0u, m0, 2)); m1 = fmaxf(m1, __shfl_xor_sync(~0u, m1, 2));
            float e0 = ex2((x0 - m0) * c2), e1 = ex2((x1 - m0) * c2), e2 = ex2((x2 - m1) * c2), e3 = ex2((x3 - m1) * c2);
            float s0 = e0 + e1, s1 = e2 + e3;
            s0 += __shfl_xor_sync(~0u, s0, 1); s1 += __shfl_xor_sync(~0u, s1, 1);
            s0 += __shfl_xor_sync(~0u, s0, 2); s1 += __shfl_xor_sync(~0u, s1, 2);
            const float r0 = rcpa(s0), r1 = rcpa(s1);
            const uint32_t pa0 = pack2(e0 * r0, e1 * r0), pa1 = pack2(e2 * r1, e3 * r1);
            #pragma unroll
            for (int J = 0; J < 4; J++) {
                float c[4][4];
                #pragma unroll
                for (int u = 0; u < 4; u++) mma1688z(c[u], pa0, pa1, vp[J * 4 + u]);
                uint4 lo = make_uint4(pack2(c[0][0], c[0][1]), pack2(c[1][0], c[1][1]), pack2(c[2][0], c[2][1]), pack2(c[3][0], c[3][1]));
                uint4 hi = make_uint4(pack2(c[0][2], c[0][3]), pack2(c[1][2], c[1][3]), pack2(c[2][2], c[2][3]), pack2(c[3][2], c[3][3]));
                *(uint4*)(orow + J * 32) = lo;
                *(uint4*)(orow + 8 * DH + J * 32) = hi;
            }
        }
    }
}

typedef CUresult (*EncodeFn)(CUtensorMap*, CUtensorMapDataType, cuuint32_t, void*, const cuuint64_t*, const cuuint64_t*,
                             const cuuint32_t*, const cuuint32_t*, CUtensorMapInterleave, CUtensorMapSwizzle,
                             CUtensorMapL2promotion, CUtensorMapFloatOOBfill);

void make_rows_map(EncodeFn enc, CUtensorMap* m, void* p, int rows) {
    cuuint32_t es[4] = {1, 1, 1, 1};
    cuuint64_t d[4] = {64, 8, 2, 8192};
    cuuint64_t s[3] = {256, 128, 2048};
    cuuint32_t b[4] = {64, 8, 2, (cuuint32_t)rows / 8};
    enc(m, CU_TENSOR_MAP_DATA_TYPE_BFLOAT16, 4, p, d, s, b, es, CU_TENSOR_MAP_INTERLEAVE_NONE, CU_TENSOR_MAP_SWIZZLE_128B,
        CU_TENSOR_MAP_L2_PROMOTION_L2_128B, CU_TENSOR_MAP_FLOAT_OOB_FILL_NONE);
}
void make_proj_map(EncodeFn enc, CUtensorMap* m, void* p, int blks) {
    cuuint32_t es[3] = {1, 1, 1};
    cuuint64_t d[3] = {64, 8, 32};
    cuuint64_t s[2] = {4096, 128};
    cuuint32_t b[3] = {64, 8, (cuuint32_t)blks};
    enc(m, CU_TENSOR_MAP_DATA_TYPE_BFLOAT16, 3, p, d, s, b, es, CU_TENSOR_MAP_INTERLEAVE_NONE, CU_TENSOR_MAP_SWIZZLE_128B,
        CU_TENSOR_MAP_L2_PROMOTION_L2_128B, CU_TENSOR_MAP_FLOAT_OOB_FILL_NONE);
}

}

extern "C" void kernel_launch(void* const* d_in, const int* in_sizes, int n_in, void* d_out, int out_size) {
    (void)in_sizes; (void)n_in; (void)out_size;
    void* fn = nullptr;
    cudaDriverEntryPointQueryResult qr;
    cudaGetDriverEntryPoint("cuTensorMapEncodeTiled", &fn, cudaEnableDefault, &qr);
    EncodeFn enc = (EncodeFn)fn;
    CUtensorMap mq, mk, mv, me, mf;
    make_rows_map(enc, &mq, d_in[0], 16);
    make_rows_map(enc, &mk, d_in[1], 64);
    make_rows_map(enc, &mv, d_in[2], 64);
    make_proj_map(enc, &me, d_in[3], 11);
    make_proj_map(enc, &mf, d_in[4], 11);
    cudaFuncSetAttribute(linformer_kernel, cudaFuncAttributeMaxDynamicSharedMemorySize, SMEM_BYTES);
    linformer_kernel<<<16 * CL, NTHR, SMEM_BYTES>>>(mk, mv, me, mf, mq, (bf16*)d_out);
}
```

```cpp
#include <cuda_runtime.h>
#include <cuda_bf16.h>
#include <cuda.h>
#include <stdint.h>

namespace {

typedef __nv_bfloat16 bf16;

constexpr int DH = 128;
constexpr int NU = 48;
constexpr int UB = 8192;
constexpr int STAGES = 10;
constexpr int NTHR = 320;
constexpr int NPRE = 4;
constexpr int NPF = 2;
constexpr int SMEM_BYTES = STAGES * UB + 8192 + 8192 + 16384 + 1024;

struct Sched { unsigned long long qm; int off; unsigned short d[4]; unsigned char tb[3], w; };
struct Params { Sched c[2]; };

__device__ __forceinline__ uint32_t smem_u32(const void* p) { return (uint32_t)__cvta_generic_to_shared(p); }
__device__ __forceinline__ void mbar_init(uint32_t bar, uint32_t cnt) { asm volatile("mbarrier.init.shared::cta.b64 [%0], %1;" :: "r"(bar), "r"(cnt) : "memory"); }
__device__ __forceinline__ void mbar_expect_tx(uint32_t bar, uint32_t bytes) { asm volatile("mbarrier.arrive.expect_tx.shared::cta.b64 _, [%0], %1;" :: "r"(bar), "r"(bytes) : "memory"); }
__device__ __forceinline__ void mbar_arrive(uint32_t bar) { asm volatile("mbarrier.arrive.shared::cta.b64 _, [%0];" :: "r"(bar) : "memory"); }
__device__ __forceinline__ void mbar_wait(uint32_t bar, uint32_t parity) {
    uint32_t done; int it = 0;
    do {
        asm volatile("{\n.reg .pred p;\nmbarrier.try_wait.parity.shared::cta.b64 p, [%1], %2;\nselp.u32 %0, 1, 0, p;\n}" : "=r"(done) : "r"(bar), "r"(parity) : "memory");
        if (++it > (1 << 22)) __trap();
    } while (!done);
}
__device__ __forceinline__ void mbar_wait_cluster(uint32_t bar) {
    uint32_t done; int it = 0;
    do {
        asm volatile("{\n.reg .pred p;\nmbarrier.try_wait.parity.acquire.cluster.shared::cta.b64 p, [%1], 0;\nselp.u32 %0, 1, 0, p;\n}" : "=r"(done) : "r"(bar) : "memory");
        if (++it > (1 << 22)) __trap();
    } while (!done);
}
__device__ __forceinline__ uint32_t mbar_test(uint32_t bar, uint32_t par) {
    uint32_t d;
    asm volatile("{\n.reg .pred p;\nmbarrier.test_wait.parity.shared::cta.b64 p, [%1], %2;\nselp.u32 %0, 1, 0, p;\n}" : "=r"(d) : "r"(bar), "r"(par) : "memory");
    return d;
}
__device__ __forceinline__ void tma4(uint32_t dst, const CUtensorMap* m, int c2, int c3, uint32_t bar, uint64_t pol) {
    asm volatile("cp.async.bulk.tensor.4d.shared::cluster.global.mbarrier::complete_tx::bytes.L2::cache_hint [%0], [%1, {%3, %3, %4, %5}], [%2], %6;"
                 :: "r"(dst), "l"(m), "r"(bar), "r"(0), "r"(c2), "r"(c3), "l"(pol) : "memory");
}
__device__ __forceinline__ void tma3(uint32_t dst, const CUtensorMap* m, int blk, uint32_t bar) {
    asm volatile("cp.async.bulk.tensor.3d.shared::cluster.global.mbarrier::complete_tx::bytes [%0], [%1, {%3, %3, %4}], [%2];"
                 :: "r"(dst), "l"(m), "r"(bar), "r"(0), "r"(blk) : "memory");
}
__device__ __forceinline__ void ldsm4(uint32_t a, uint32_t& r0, uint32_t& r1, uint32_t& r2, uint32_t& r3) {
    asm volatile("ldmatrix.sync.aligned.m8n8.x4.shared.b16 {%0,%1,%2,%3}, [%4];" : "=r"(r0), "=r"(r1), "=r"(r2), "=r"(r3) : "r"(a) : "memory");
}
__device__ __forceinline__ void ldsm4t(uint32_t a, uint32_t& r0, uint32_t& r1, uint32_t& r2, uint32_t& r3) {
    asm volatile("ldmatrix.sync.aligned.m8n8.x4.trans.shared.b16 {%0,%1,%2,%3}, [%4];" : "=r"(r0), "=r"(r1), "=r"(r2), "=r"(r3) : "r"(a) : "memory");
}
__device__ __forceinline__ void mma16816(float* c, uint32_t a0, uint32_t a1, uint32_t a2, uint32_t a3, uint32_t b0, uint32_t b1) {
    asm volatile("mma.sync.aligned.m16n8k16.row.col.f32.bf16.bf16.f32 {%0,%1,%2,%3}, {%4,%5,%6,%7}, {%8,%9}, {%0,%1,%2,%3};"
                 : "+f"(c[0]), "+f"(c[1]), "+f"(c[2]), "+f"(c[3]) : "r"(a0), "r"(a1), "r"(a2), "r"(a3), "r"(b0), "r"(b1));
}
__device__ __forceinline__ void mma1688z(float* c, uint32_t a0, uint32_t a1, uint32_t b0) {
    asm volatile("mma.sync.aligned.m16n8k8.row.col.f32.bf16.bf16.f32 {%0,%1,%2,%3}, {%4,%5}, {%6}, {%7,%7,%7,%7};"
                 : "=f"(c[0]), "=f"(c[1]), "=f"(c[2]), "=f"(c[3]) : "r"(a0), "r"(a1), "r"(b0), "f"(0.f));
}
__device__ __forceinline__ uint32_t pack2(float lo, float hi) { uint32_t r; asm("cvt.rn.bf16x2.f32 %0, %1, %2;" : "=r"(r) : "f"(hi), "f"(lo)); return r; }
__device__ __forceinline__ float ex2(float x) { float y; asm("ex2.approx.ftz.f32 %0, %1;" : "=f"(y) : "f"(x)); return y; }
__device__ __forceinline__ float rcpa(float x) { float y; asm("rcp.approx.ftz.f32 %0, %1;" : "=f"(y) : "f"(x)); return y; }
__device__ __forceinline__ uint32_t mapa(uint32_t a, int r) { uint32_t o; asm("mapa.shared::cluster.u32 %0, %1, %2;" : "=r"(o) : "r"(a), "r"(r)); return o; }
__device__ __forceinline__ bool elect_one() { uint32_t p; asm volatile("{\n.reg .pred P;\nelect.sync _|P, 0xffffffff;\nselp.u32 %0, 1, 0, P;\n}" : "=r"(p)); return p; }
__device__ __forceinline__ void st_async4(uint32_t a, uint32_t x, uint32_t y, uint32_t z, uint32_t w, uint32_t b) {
    asm volatile("st.async.weak.shared::cluster.mbarrier::complete_tx::bytes.v4.b32 [%0], {%1,%2,%3,%4}, [%5];" :: "r"(a), "r"(x), "r"(y), "r"(z), "r"(w), "r"(b) : "memory");
}
__device__ __forceinline__ float4 lds4(uint32_t a) { float4 x; asm volatile("ld.shared.v4.f32 {%0,%1,%2,%3}, [%4];" : "=f"(x.x), "=f"(x.y), "=f"(x.z), "=f"(x.w) : "r"(a) : "memory"); return x; }
__device__ __forceinline__ float2 lds2(uint32_t a) { float2 x; asm volatile("ld.shared.v2.f32 {%0,%1}, [%2];" : "=f"(x.x), "=f"(x.y) : "r"(a) : "memory"); return x; }
__device__ __forceinline__ uint4 ldsu4(uint32_t a) { uint4 x; asm volatile("ld.shared.v4.u32 {%0,%1,%2,%3}, [%4];" : "=r"(x.x), "=r"(x.y), "=r"(x.z), "=r"(x.w) : "r"(a) : "memory"); return x; }

__global__ void __launch_bounds__(NTHR, 2)
linformer_kernel(const char* __restrict__ kptr, const char* __restrict__ vptr, bf16* __restrict__ out, const __grid_constant__ Params pp,
                 const __grid_constant__ CUtensorMap mk, const __grid_constant__ CUtensorMap mv,
                 const __grid_constant__ CUtensorMap me, const __grid_constant__ CUtensorMap mf,
                 const __grid_constant__ CUtensorMap mq) {
    const int b = blockIdx.x;
    const int grp = b >> 4, j = b & 15;
    const int isv = j >> 3, dh = (j >> 2) & 1, nh = j & 3;
    const int kvr = grp * 1024 + nh * 64;
    uint64_t pol;
    asm volatile("createpolicy.fractional.L2::evict_first.b64 %0, 1.0;" : "=l"(pol));
    const int tid = threadIdx.x, lane = tid & 31;
    if (tid == 32) {
        #pragma unroll
        for (int i = 0; i < NPF; i++)
            asm volatile("cp.async.bulk.prefetch.L2.global.L2::cache_hint [%0], %1, %2;"
                         :: "l"((isv ? vptr : kptr) + (size_t)(kvr + (2 * i + dh) * 8) * 2048), "r"(16384), "l"(pol) : "memory");
    }
    extern __shared__ __align__(1024) char smem_raw[];
    const uint32_t sbase = smem_u32(smem_raw);
    const uint32_t sproj = sbase + STAGES * UB, srecv = sproj + 8192, sfrag = srecv + 8192;
    const uint32_t bfull = sfrag + 16384, bempty = bfull + 8 * STAGES, bproj = bempty + 8 * STAGES, bfl = bproj + 8, bfr = bfl + 32;
    const int warp = __shfl_sync(~0u, tid >> 5, 0);
    const CUtensorMap* mkv = isv ? &mv : &mk;
    const bool el = elect_one();
    const int cls = grp == 7;
    if (warp == 0) {
        unsigned tz; asm volatile("mov.u32 %0, %%globaltimer_lo;" : "=r"(tz));
        if (el) {
            #pragma unroll
            for (int p = 0; p < NPRE; p++) mbar_init(bfull + 8 * p, 1);
            mbar_init(bproj, 1);
            #pragma unroll
            for (int p = 0; p < NPRE; p++) {
                mbar_expect_tx(bfull + 8 * p, UB);
                tma4(sbase + p * UB, mkv, dh, kvr + p * 8, bfull + 8 * p, pol);
                if (p == 1) { mbar_expect_tx(bproj, 8192); tma3(sproj, isv ? &mf : &me, nh * 8, bproj); }
            }
        }
        asm volatile("bar.arrive 2, 128;" ::: "memory");
        if (el) asm volatile("prefetch.tensormap [%0];" :: "l"(&mq) : "memory");
        const Sched& sc = pp.c[cls];
        unsigned long long m = sc.qm >> NPRE;
        unsigned dl = tz + sc.off + NPRE * sc.d[0];
        int ck = kvr + NPRE * 8, cq = grp * 1024 + j * 16;
        int s = NPRE, su = NPRE - sc.w + STAGES;
        unsigned ph = 1, phu = 1;
        if (su >= STAGES) { su -= STAGES; phu = 0; }
        unsigned dd = sc.d[0];
        const int tb0 = sc.tb[0], tb1 = sc.tb[1], tb2 = sc.tb[2];
        const unsigned d1 = sc.d[1], d2 = sc.d[2], d3 = sc.d[3];
        asm volatile("bar.sync 1, %0;" :: "n"(NTHR) : "memory");
        asm volatile("barrier.cluster.arrive.relaxed.aligned;" ::: "memory");
        #pragma unroll 1
        for (int t = NPRE; t < NU; t++) {
            const bool isq = m & 1; m >>= 1;
            const CUtensorMap* mp = isq ? &mq : mkv;
            const int c2 = isq ? 0 : dh, c3 = isq ? cq : ck;
            int it = 0;
            while (true) {
                const uint32_t slot_free = mbar_test(bempty + 8 * s, ph), landed = mbar_test(bfull + 8 * su, phu);
                unsigned now; asm volatile("mov.u32 %0, %%globaltimer_lo;" : "=r"(now));
                if (slot_free && landed && (int)(now - dl) >= 0) break;
                if (++it > (1 << 22)) __trap();
            }
            if (el) {
                mbar_expect_tx(bfull + 8 * s, UB);
                tma4(sbase + s * UB, mp, c2, c3, bfull + 8 * s, pol);
            }
            if (isq) { cq += 4; if ((cq & 15) == 0) cq += 240; } else { ck += 8; if ((ck & 63) == 0) ck += 192; }
            if (t == tb0) dd = d1;
            if (t == tb1) dd = d2;
            if (t == tb2) dd = d3;
            dl += dd;
            if (++s == STAGES) { s = 0; ph ^= 1; }
            if (++su == STAGES) { su = 0; phu ^= 1; }
        }
        asm volatile("barrier.cluster.wait.aligned;" ::: "memory");
        return;
    }
    const unsigned long long qm = pp.c[cls].qm;
    if (warp <= 3) {
        asm volatile("bar.sync 2, 128;" ::: "memory");
        if (el) {
            if (warp == 1) {
                #pragma unroll
                for (int i = 0; i < STAGES; i++) mbar_init(bempty + 8 * i, 4);
            } else if (warp == 2) {
                #pragma unroll
                for (int i = NPRE; i < STAGES; i++) mbar_init(bfull + 8 * i, 1);
                #pragma unroll
                for (int i = 0; i < 4; i++) mbar_init(bfl + 8 * i, 1);
                #pragma unroll
                for (int i = 0; i < 4; i++) mbar_expect_tx(bfl + 8 * i, 2048);
                asm volatile("fence.mbarrier_init.release.cluster;" ::: "memory");
            } else {
                #pragma unroll
                for (int i = 0; i < 4; i++) mbar_init(bfr + 16 * i, 1);
                #pragma unroll
                for (int i = 0; i < 4; i++) mbar_expect_tx(bfr + 16 * i, 4096);
                asm volatile("fence.mbarrier_init.release.cluster;" ::: "memory");
            }
        }
    }
    asm volatile("bar.sync 1, %0;" :: "n"(NTHR) : "memory");
    asm volatile("barrier.cluster.arrive.relaxed.aligned;" ::: "memory");
    const int g = lane >> 2, tq = lane & 3;
    const int mi = lane >> 3, li = lane & 7;
    if (warp == 5) {
        const int odd = lane & 1;
        const uint32_t ad0 = isv ? srecv + ((4 * odd + ((lane >> 3) & 1)) * 4 + ((lane >> 1) & 3)) * 16 + (lane >> 4) * 8 : srecv + lane * 16;
        uint32_t rbase[8];
        #pragma unroll
        for (int rr = 0; rr < 8; rr++) rbase[rr] = mapa(sbase, (2 * rr + odd + j + 1) & 15) - sbase;
        const uint32_t la0 = sfrag + j * 256 + (lane >> 1) * 16;
        asm volatile("barrier.cluster.wait.aligned;" ::: "memory");
        #pragma unroll 1
        for (int hg = 0; hg < 4; hg++) {
            const uint32_t ad = ad0 + hg * 2048;
            mbar_wait_cluster(bfl + hg * 8);
            uint32_t o0, o1;
            if (!isv) {
                float4 x = lds4(ad), y = lds4(ad + 512), z = lds4(ad + 1024), v = lds4(ad + 1536);
                uint32_t k0 = pack2((x.x + y.x) + (z.x + v.x), (x.y + y.y) + (z.y + v.y));
                uint32_t k1 = pack2((x.z + y.z) + (z.z + v.z), (x.w + y.w) + (z.w + v.w));
                asm volatile("movmatrix.sync.aligned.m8n8.trans.b16 %0, %1;" : "=r"(o0) : "r"(k0));
                asm volatile("movmatrix.sync.aligned.m8n8.trans.b16 %0, %1;" : "=r"(o1) : "r"(k1));
            } else {
                float2 x = lds2(ad), y = lds2(ad + 512), z = lds2(ad + 1024), v = lds2(ad + 1536);
                float2 x2 = lds2(ad + 128), y2 = lds2(ad + 640), z2 = lds2(ad + 1152), v2 = lds2(ad + 1664);
                o0 = pack2((x.x + y.x) + (z.x + v.x), (x.y + y.y) + (z.y + v.y));
                o1 = pack2((x2.x + y2.x) + (z2.x + v2.x), (x2.y + y2.y) + (z2.y + v2.y));
            }
            const uint32_t p0 = __shfl_xor_sync(~0u, o0, 1), p1 = __shfl_xor_sync(~0u, o1, 1);
            const uint32_t w0 = odd ? p0 : o0, w1 = odd ? p1 : o1, w2 = odd ? o0 : p0, w3 = odd ? o1 : p1;
            const uint32_t la = la0 + hg * 4096, lb = bfr + hg * 16;
            #pragma unroll
            for (int rr = 0; rr < 8; rr++) st_async4(la + rbase[rr], w0, w1, w2, w3, lb + rbase[rr]);
        }
        return;
    }
    const int w = (warp - 1 - (warp > 5)) & 3;
    int n0 = w >> 1, n1 = 14;
    if (warp < 5) {
        const int dr = (j & 12) | w;
        const uint32_t ra = mapa(srecv + nh * 512 + lane * 16, dr), rb = mapa(bfl, dr);
        const uint32_t aoff = sbase + ((mi >> 1) * 8 + li) * 128 + (((2 * w + (mi & 1)) ^ li) << 4);
        const uint32_t boff = sproj + li * 128 + ((mi ^ li) << 4);
        unsigned long long m = ~qm, gm = qm << STAGES;
        int s = 0; unsigned par = 0;
        asm volatile("barrier.cluster.wait.aligned;" ::: "memory");
        mbar_wait(bproj, 0);
        #pragma unroll 1
        for (int hg = 0; hg < 4; hg++) {
            float acc[2][4] = {};
            #pragma unroll 1
            for (int i = 0; i < 8; i++) {
                uint32_t bb[8];
                ldsm4(boff + i * 1024, bb[0], bb[1], bb[2], bb[3]);
                ldsm4((boff ^ 64) + i * 1024, bb[4], bb[5], bb[6], bb[7]);
                if (gm & 1) mbar_wait(bempty + 8 * s, par ^ 1);
                mbar_wait(bfull + 8 * s, par);
                uint32_t a[4][4];
                #pragma unroll
                for (int ks = 0; ks < 4; ks++) ldsm4t(aoff + s * UB + ks * 2048, a[ks][0], a[ks][1], a[ks][2], a[ks][3]);
                #pragma unroll
                for (int ks = 0; ks < 4; ks++) mma16816(acc[ks & 1], a[ks][0], a[ks][1], a[ks][2], a[ks][3], bb[2 * ks], bb[2 * ks + 1]);
                if (i == 7)
                    st_async4(ra + hg * 2048, __float_as_uint(acc[0][0] + acc[1][0]), __float_as_uint(acc[0][1] + acc[1][1]),
                              __float_as_uint(acc[0][2] + acc[1][2]), __float_as_uint(acc[0][3] + acc[1][3]), rb + hg * 8);
                __syncwarp();
                if (lane == 0) mbar_arrive(bempty + 8 * s);
                const int dt = __ffs((unsigned)(m >> 1));
                m >>= dt; gm >>= dt; s += dt;
                if (s >= STAGES) { s -= STAGES; par ^= 1; }
            }
        }
        n0 += 14; n1 = 16;
    } else {
        asm volatile("barrier.cluster.wait.aligned;" ::: "memory");
    }
    const int rg = w & 1;
    const uint32_t qoff = sbase + (rg * 2 + (mi & 1)) * 2048 + li * 128;
    const uint32_t qx = (mi >> 1) ^ li;
    bf16* obase = out + ((size_t)(grp * 512 + j * 8 + rg) * 16 + g) * DH + tq * 8;
    uint32_t kp[16], vp[16];
    unsigned long long m = qm;
    if (warp < 5) m = 3ull << 46;
    if (w & 2) m &= m - 1;
    #pragma unroll 1
    for (int n = n0; n < n1; n += 2) {
        const int t = __ffsll(m) - 1; m &= m - 1; m &= m - 1;
        const int r = (t * 26) >> 8, s = t - r * STAGES;
        const unsigned par = r & 1;
        const int hg = n >> 2;
        bf16* orow = obase + (size_t)(n * 2 + hg * 120) * 16 * DH;
        if (t >= STAGES) mbar_wait(bempty + 8 * s, par ^ 1);
        mbar_wait(bfull + 8 * s, par);
        uint32_t a[8][4];
        #pragma unroll
        for (int ks = 0; ks < 8; ks++) ldsm4(qoff + s * UB + (ks >> 2) * 1024 + ((qx ^ ((ks & 3) << 1)) << 4), a[ks][0], a[ks][1], a[ks][2], a[ks][3]);
        if ((n & 2) == 0 || n == n0) {
            mbar_wait_cluster(bfr + 16 * hg);
            #pragma unroll
            for (int i = 0; i < 8; i++)
                asm volatile("ld.shared.v2.u32 {%0,%1}, [%2];" : "=r"(kp[2 * i]), "=r"(kp[2 * i + 1]) : "r"(sfrag + hg * 4096 + i * 256 + lane * 8) : "memory");
            #pragma unroll
            for (int i = 0; i < 4; i++) { uint4 x = ldsu4(sfrag + hg * 4096 + 2048 + i * 512 + lane * 16); vp[4 * i] = x.x; vp[4 * i + 1] = x.y; vp[4 * i + 2] = x.z; vp[4 * i + 3] = x.w; }
        }
        float sc[4][4] = {};
        #pragma unroll
        for (int ks = 0; ks < 8; ks++) mma16816(sc[ks & 3], a[ks][0], a[ks][1], a[ks][2], a[ks][3], kp[2 * ks], kp[2 * ks + 1]);
        __syncwarp();
        if (lane < 2) mbar_arrive(bempty + 8 * s);
        const float c2 = 0.08838834764831845f * 1.4426950408889634f;
        float x0 = sc[0][0] + sc[1][0], x1 = sc[0][1] + sc[1][1], x2 = sc[0][2] + sc[1][2], x3 = sc[0][3] + sc[1][3];
        x0 += sc[2][0] + sc[3][0]; x1 += sc[2][1] + sc[3][1]; x2 += sc[2][2] + sc[3][2]; x3 += sc[2][3] + sc[3][3];
        float m0 = fmaxf(x0, x1), m1 = fmaxf(x2, x3);
        m0 = fmaxf(m0, __shfl_xor_sync(~0u, m0, 1)); m1 = fmaxf(m1, __shfl_xor_sync(~0u, m1, 1));
        m0 = fmaxf(m0, __shfl_xor_sync(~0u, m0, 2)); m1 = fmaxf(m1, __shfl_xor_sync(~0u, m1, 2));
        const float e0 = ex2((x0 - m0) * c2), e1 = ex2((x1 - m0) * c2), e2 = ex2((x2 - m1) * c2), e3 = ex2((x3 - m1) * c2);
        float s0 = e0 + e1, s1 = e2 + e3;
        s0 += __shfl_xor_sync(~0u, s0, 1); s1 += __shfl_xor_sync(~0u, s1, 1);
        s0 += __shfl_xor_sync(~0u, s0, 2); s1 += __shfl_xor_sync(~0u, s1, 2);
        const float r0 = rcpa(s0), r1 = rcpa(s1);
        const uint32_t pa0 = pack2(e0 * r0, e1 * r0), pa1 = pack2(e2 * r1, e3 * r1);
        #pragma unroll
        for (int J = 0; J < 4; J++) {
            float c[4][4];
            #pragma unroll
            for (int u = 0; u < 4; u++) mma1688z(c[u], pa0, pa1, vp[J * 4 + u]);
            *(uint4*)(orow + J * 32) = make_uint4(pack2(c[0][0], c[0][1]), pack2(c[1][0], c[1][1]), pack2(c[2][0], c[2][1]), pack2(c[3][0], c[3][1]));
            *(uint4*)(orow + 8 * DH + J * 32) = make_uint4(pack2(c[0][2], c[0][3]), pack2(c[1][2], c[1][3]), pack2(c[2][2], c[2][3]), pack2(c[3][2], c[3][3]));
        }
    }
}

typedef CUresult (*EncodeFn)(CUtensorMap*, CUtensorMapDataType, cuuint32_t, void*, const cuuint64_t*, const cuuint64_t*,
                             const cuuint32_t*, const cuuint32_t*, CUtensorMapInterleave, CUtensorMapSwizzle,
                             CUtensorMapL2promotion, CUtensorMapFloatOOBfill);

void make_rows_map(EncodeFn enc, CUtensorMap* m, void* p, int halves, int groups) {
    cuuint32_t es[4] = {1, 1, 1, 1};
    cuuint64_t d[4] = {64, 8, 2, 8192};
    cuuint64_t s[3] = {256, 128, 2048};
    cuuint32_t b[4] = {64, 8, (cuuint32_t)halves, (cuuint32_t)groups};
    enc(m, CU_TENSOR_MAP_DATA_TYPE_BFLOAT16, 4, p, d, s, b, es, CU_TENSOR_MAP_INTERLEAVE_NONE, CU_TENSOR_MAP_SWIZZLE_128B,
        CU_TENSOR_MAP_L2_PROMOTION_L2_128B, CU_TENSOR_MAP_FLOAT_OOB_FILL_NONE);
}
void make_proj_map(EncodeFn enc, CUtensorMap* m, void* p) {
    cuuint32_t es[3] = {1, 1, 1};
    cuuint64_t d[3] = {64, 8, 32};
    cuuint64_t s[2] = {4096, 128};
    cuuint32_t b[3] = {64, 8, 8};
    enc(m, CU_TENSOR_MAP_DATA_TYPE_BFLOAT16, 3, p, d, s, b, es, CU_TENSOR_MAP_INTERLEAVE_NONE, CU_TENSOR_MAP_SWIZZLE_128B,
        CU_TENSOR_MAP_L2_PROMOTION_L2_128B, CU_TENSOR_MAP_FLOAT_OOB_FILL_NONE);
}
Sched make_sched(int f, int l, int w, int off, int d0, int d1, int d2, int d3) {
    Sched s = {};
    const int rk = 32 - f, rq = l - f + 1 - rk;
    int pos = f, k = 0;
    for (int q = 0; q < rq; q++) {
        s.qm |= 1ull << pos++;
        for (const int upto = rk * (q + 1) / rq; k < upto; k++) pos++;
    }
    for (; pos < NU; pos++) s.qm |= 1ull << pos;
    s.off = off; s.w = (unsigned char)w;
    s.d[0] = (unsigned short)d0; s.d[1] = (unsigned short)d1; s.d[2] = (unsigned short)d2; s.d[3] = (unsigned short)d3;
    s.tb[0] = (unsigned char)f; s.tb[1] = (unsigned char)((f + l) / 2); s.tb[2] = (unsigned char)l;
    return s;
}

}

extern "C" void kernel_launch(void* const* d_in, const int* in_sizes, int n_in, void* d_out, int out_size) {
    (void)in_sizes; (void)n_in; (void)out_size;
    void* fn = nullptr;
    cudaDriverEntryPointQueryResult qr;
    cudaGetDriverEntryPoint("cuTensorMapEncodeTiled", &fn, cudaEnableDefault, &qr);
    EncodeFn enc = (EncodeFn)fn;
    CUtensorMap mq, mk, mv, me, mf;
    make_rows_map(enc, &mq, d_in[0], 2, 4);
    make_rows_map(enc, &mk, d_in[1], 1, 8);
    make_rows_map(enc, &mv, d_in[2], 1, 8);
    make_proj_map(enc, &me, d_in[3]);
    make_proj_map(enc, &mf, d_in[4]);
    Params pp;
    pp.c[0] = make_sched(9, 42, 7, -696, 333, 333, 336, 336);
    pp.c[1] = make_sched(9, 42, 8, -596, 329, 293, 311, 281);
    cudaFuncSetAttribute(linformer_kernel, cudaFuncAttributeMaxDynamicSharedMemorySize, SMEM_BYTES);
    cudaFuncSetAttribute(linformer_kernel, cudaFuncAttributeNonPortableClusterSizeAllowed, 1);
    cudaLaunchConfig_t cfg = {};
    cfg.gridDim = dim3(128);
    cfg.blockDim = dim3(NTHR);
    cfg.dynamicSmemBytes = SMEM_BYTES;
    cfg.stream = cudaStreamPerThread;
    cudaLaunchAttribute at[2];
    at[0].id = cudaLaunchAttributeClusterDimension;
    at[0].val.clusterDim.x = 16; at[0].val.clusterDim.y = 1; at[0].val.clusterDim.z = 1;
    at[1].id = cudaLaunchAttributeClusterSchedulingPolicyPreference;
    at[1].val.clusterSchedulingPolicyPreference = cudaClusterSchedulingPolicyLoadBalancing;
    cfg.attrs = at; cfg.numAttrs = 2;
    cudaLaunchKernelEx(&cfg, linformer_kernel, (const char*)d_in[1], (const char*)d_in[2], (bf16*)d_out, pp, mk, mv, me, mf, mq);
}
```

```cpp
#include <cuda_runtime.h>
#include <cuda_bf16.h>
#include <cuda.h>
#include <stdint.h>

namespace lf {

typedef __nv_bfloat16 bf16;

constexpr int DH = 128;
constexpr int NU = 48;
constexpr int UB = 8192;
constexpr int STAGES = 10;
constexpr int NTHR = 320;
constexpr int NPRE = 4;
constexpr int SMEM_BYTES = STAGES * UB + 8192 + 8192 + 16384 + 1024;

constexpr int NSEG = 7;

struct Sched { unsigned long long qm, seg0, seg1; int off; unsigned short slack, w; };
struct Params {
    const char* kv[2];
    bf16* out;
    Sched c[2];
};

__device__ __forceinline__ uint32_t smem_u32(const void* p) { return (uint32_t)__cvta_generic_to_shared(p); }
__device__ __forceinline__ void mbar_init(uint32_t bar, uint32_t cnt) { asm volatile("mbarrier.init.shared::cta.b64 [%0], %1;" :: "r"(bar), "r"(cnt) : "memory"); }
__device__ __forceinline__ void mbar_expect_tx(uint32_t bar, uint32_t bytes) { asm volatile("mbarrier.arrive.expect_tx.shared::cta.b64 _, [%0], %1;" :: "r"(bar), "r"(bytes) : "memory"); }
__device__ __forceinline__ void mbar_arrive(uint32_t bar) { asm volatile("mbarrier.arrive.shared::cta.b64 _, [%0];" :: "r"(bar) : "memory"); }
__device__ __forceinline__ void mbar_wait(uint32_t bar, uint32_t parity) {
    uint32_t done; int it = 0;
    do {
        asm volatile("{\n.reg .pred p;\nmbarrier.try_wait.parity.shared::cta.b64 p, [%1], %2;\nselp.u32 %0, 1, 0, p;\n}" : "=r"(done) : "r"(bar), "r"(parity) : "memory");
        if (++it > (1 << 22)) __trap();
    } while (!done);
}
__device__ __forceinline__ void mbar_wait_cluster(uint32_t bar) {
    uint32_t done; int it = 0;
    do {
        asm volatile("{\n.reg .pred p;\nmbarrier.try_wait.parity.acquire.cluster.shared::cta.b64 p, [%1], 0;\nselp.u32 %0, 1, 0, p;\n}" : "=r"(done) : "r"(bar) : "memory");
        if (++it > (1 << 22)) __trap();
    } while (!done);
}
__device__ __forceinline__ uint32_t mbar_test(uint32_t bar, uint32_t par) {
    uint32_t d;
    asm volatile("{\n.reg .pred p;\nmbarrier.test_wait.parity.shared::cta.b64 p, [%1], %2;\nselp.u32 %0, 1, 0, p;\n}" : "=r"(d) : "r"(bar), "r"(par) : "memory");
    return d;
}
__device__ __forceinline__ void tma_load4(uint32_t dst, const CUtensorMap* m, int c2, int c3, uint32_t bar, uint64_t pol) {
    asm volatile("cp.async.bulk.tensor.4d.shared::cluster.global.mbarrier::complete_tx::bytes.L2::cache_hint [%0], [%1, {%3, %3, %4, %5}], [%2], %6;"
                 :: "r"(dst), "l"(m), "r"(bar), "r"(0), "r"(c2), "r"(c3), "l"(pol) : "memory");
}
__device__ __forceinline__ void tma_load3(uint32_t dst, const CUtensorMap* m, int blk, uint32_t bar) {
    asm volatile("cp.async.bulk.tensor.3d.shared::cluster.global.mbarrier::complete_tx::bytes [%0], [%1, {%3, %3, %4}], [%2];"
                 :: "r"(dst), "l"(m), "r"(bar), "r"(0), "r"(blk) : "memory");
}
__device__ __forceinline__ void ldsm4(uint32_t a, uint32_t& r0, uint32_t& r1, uint32_t& r2, uint32_t& r3) {
    asm volatile("ldmatrix.sync.aligned.m8n8.x4.shared.b16 {%0,%1,%2,%3}, [%4];" : "=r"(r0), "=r"(r1), "=r"(r2), "=r"(r3) : "r"(a) : "memory");
}
__device__ __forceinline__ void ldsm4t(uint32_t a, uint32_t& r0, uint32_t& r1, uint32_t& r2, uint32_t& r3) {
    asm volatile("ldmatrix.sync.aligned.m8n8.x4.trans.shared.b16 {%0,%1,%2,%3}, [%4];" : "=r"(r0), "=r"(r1), "=r"(r2), "=r"(r3) : "r"(a) : "memory");
}
__device__ __forceinline__ void mma16816(float* c, uint32_t a0, uint32_t a1, uint32_t a2, uint32_t a3, uint32_t b0, uint32_t b1) {
    asm volatile("mma.sync.aligned.m16n8k16.row.col.f32.bf16.bf16.f32 {%0,%1,%2,%3}, {%4,%5,%6,%7}, {%8,%9}, {%0,%1,%2,%3};"
                 : "+f"(c[0]), "+f"(c[1]), "+f"(c[2]), "+f"(c[3]) : "r"(a0), "r"(a1), "r"(a2), "r"(a3), "r"(b0), "r"(b1));
}
__device__ __forceinline__ void mma1688z(float* c, uint32_t a0, uint32_t a1, uint32_t b0) {
    asm volatile("mma.sync.aligned.m16n8k8.row.col.f32.bf16.bf16.f32 {%0,%1,%2,%3}, {%4,%5}, {%6}, {%7,%7,%7,%7};"
                 : "=f"(c[0]), "=f"(c[1]), "=f"(c[2]), "=f"(c[3]) : "r"(a0), "r"(a1), "r"(b0), "f"(0.f));
}
__device__ __forceinline__ uint32_t pack2(float lo, float hi) { uint32_t r; asm("cvt.rn.bf16x2.f32 %0, %1, %2;" : "=r"(r) : "f"(hi), "f"(lo)); return r; }
__device__ __forceinline__ float ex2(float x) { float y; asm("ex2.approx.ftz.f32 %0, %1;" : "=f"(y) : "f"(x)); return y; }
__device__ __forceinline__ uint32_t max2(uint32_t a, uint32_t b) { uint32_t r; asm("max.NaN.bf16x2 %0, %1, %2;" : "=r"(r) : "r"(a), "r"(b)); return r; }
__device__ __forceinline__ float bf_lo(uint32_t u) { return __uint_as_float(u << 16); }
__device__ __forceinline__ float bf_hi(uint32_t u) { return __uint_as_float(u & 0xffff0000u); }
__device__ __forceinline__ float rcpa(float x) { float y; asm("rcp.approx.ftz.f32 %0, %1;" : "=f"(y) : "f"(x)); return y; }
__device__ __forceinline__ uint32_t mapa(uint32_t a, int r) { uint32_t o; asm("mapa.shared::cluster.u32 %0, %1, %2;" : "=r"(o) : "r"(a), "r"(r)); return o; }
__device__ __forceinline__ bool elect_one() { uint32_t p; asm volatile("{\n.reg .pred P;\nelect.sync _|P, 0xffffffff;\nselp.u32 %0, 1, 0, P;\n}" : "=r"(p)); return p; }
__device__ __forceinline__ void st_async4(uint32_t a, uint32_t x, uint32_t y, uint32_t z, uint32_t w, uint32_t b) {
    asm volatile("st.async.weak.shared::cluster.mbarrier::complete_tx::bytes.v4.b32 [%0], {%1,%2,%3,%4}, [%5];" :: "r"(a), "r"(x), "r"(y), "r"(z), "r"(w), "r"(b) : "memory");
}
__device__ __forceinline__ float4 lds4(uint32_t a) { float4 x; asm volatile("ld.shared.v4.f32 {%0,%1,%2,%3}, [%4];" : "=f"(x.x), "=f"(x.y), "=f"(x.z), "=f"(x.w) : "r"(a) : "memory"); return x; }
__device__ __forceinline__ float2 lds2(uint32_t a) { float2 x; asm volatile("ld.shared.v2.f32 {%0,%1}, [%2];" : "=f"(x.x), "=f"(x.y) : "r"(a) : "memory"); return x; }
__device__ __forceinline__ uint4 ldsu4(uint32_t a) { uint4 x; asm volatile("ld.shared.v4.u32 {%0,%1,%2,%3}, [%4];" : "=r"(x.x), "=r"(x.y), "=r"(x.z), "=r"(x.w) : "r"(a) : "memory"); return x; }

__global__ void __launch_bounds__(NTHR, 2)
linformer_kernel(const __grid_constant__ Params pp,
                 const __grid_constant__ CUtensorMap mk, const __grid_constant__ CUtensorMap mv,
                 const __grid_constant__ CUtensorMap me, const __grid_constant__ CUtensorMap mf,
                 const __grid_constant__ CUtensorMap mq) {
    const uint64_t pol = 0x12F0000000000000ull;
    const unsigned b = blockIdx.x;
    const int tid = threadIdx.x, lane = tid & 31;
    if (tid == 32)
        asm volatile("cp.async.bulk.prefetch.L2.global.L2::cache_hint [%0], %1, %2;"
                     :: "l"(pp.kv[b & 1] + (((b >> 4) << 21) | ((b & 12) << 15) | ((b & 2) << 14))), "r"(NPRE * UB), "l"(pol) : "memory");
    const int grp = b >> 4, j = b & 15;
    const int isv = j & 1, dh = (j >> 1) & 1, nh = j >> 2;
    const int kvr = grp * 1024 + nh * 64;
    extern __shared__ __align__(1024) char smem_raw[];
    const uint32_t sbase = smem_u32(smem_raw);
    const uint32_t sproj = sbase + STAGES * UB, srecv = sproj + 8192, sfrag = srecv + 8192;
    const uint32_t bfull = sfrag + 16384, bempty = bfull + 8 * STAGES, bproj = bempty + 8 * STAGES, bfl = bproj + 8, bfr = bfl + 32;
    const int warp = __shfl_sync(~0u, tid >> 5, 0);
    const CUtensorMap* mkv = isv ? &mv : &mk;
    const bool el = elect_one();
    const int cls = grp == 7;
    if (warp == 0) {
        unsigned tz; asm volatile("mov.u32 %0, %%globaltimer_lo;" : "=r"(tz));
        if (el) {
            #pragma unroll
            for (int p = 0; p < NPRE; p++) mbar_init(bfull + 8 * p, 1);
            mbar_init(bproj, 1);
            #pragma unroll
            for (int p = 0; p < NPRE; p++) {
                mbar_expect_tx(bfull + 8 * p, UB);
                tma_load4(sbase + p * UB, mkv, dh, kvr + p * 8, bfull + 8 * p, pol);
                if (p == 1) { mbar_expect_tx(bproj, 8192); tma_load3(sproj, isv ? &mf : &me, nh * 8, bproj); }
            }
        }
        asm volatile("bar.arrive 2, 128;" ::: "memory");
        if (el) asm volatile("prefetch.tensormap [%0];" :: "l"(&mq) : "memory");
        const Sched& sc = pp.c[cls];
        unsigned long long m = sc.qm >> NPRE;
        unsigned long long sg0 = sc.seg0, sg1 = sc.seg1;
        unsigned dl = tz + sc.off;
        const unsigned slack = sc.slack;
        int ck = kvr + NPRE * 8, cq = grp * 1024 + j * 16;
        int s = NPRE, su = NPRE - sc.w + STAGES;
        unsigned ph = 1, phu = 1;
        if (su >= STAGES) { su -= STAGES; phu = 0; }
        asm volatile("bar.sync 1, %0;" :: "n"(NTHR) : "memory");
        asm volatile("barrier.cluster.arrive.relaxed.aligned;" ::: "memory");
        #pragma unroll 1
        for (int t = NPRE; t < NU; t++) {
            const bool isq = m & 1; m >>= 1;
            const CUtensorMap* mp = isq ? &mq : mkv;
            const int c2 = isq ? 0 : dh, c3 = isq ? cq : ck;
            int it = 0;
            unsigned now;
            while (true) {
                const uint32_t slot_free = mbar_test(bempty + 8 * s, ph), landed = mbar_test(bfull + 8 * su, phu);
                asm volatile("mov.u32 %0, %%globaltimer_lo;" : "=r"(now));
                if (slot_free && landed && (int)(now - dl) >= 0) break;
                if (++it > (1 << 22)) __trap();
            }
            if (el) {
                mbar_expect_tx(bfull + 8 * s, UB);
                tma_load4(sbase + s * UB, mp, c2, c3, bfull + 8 * s, pol);
            }
            if (isq) { cq += 4; if ((cq & 15) == 0) cq += 240; } else { ck += 8; if ((ck & 63) == 0) ck += 192; }
            if (t == (int)(((unsigned)sg0 >> 10) & 63)) { sg0 = (sg0 >> 16) | (sg1 << 48); sg1 >>= 16; }
            if ((int)(now - slack - dl) > 0) dl = now - slack;
            dl += ((unsigned)sg0 & 1023) * 2;
            if (++s == STAGES) { s = 0; ph ^= 1; }
            if (++su == STAGES) { su = 0; phu ^= 1; }
        }
        asm volatile("barrier.cluster.wait.aligned;" ::: "memory");
        return;
    }
    const unsigned long long qm = pp.c[cls].qm;
    if (warp <= 3) {
        asm volatile("bar.sync 2, 128;" ::: "memory");
        if (el) {
            if (warp == 1) {
                #pragma unroll
                for (int i = 0; i < STAGES; i++) mbar_init(bempty + 8 * i, 4);
            } else if (warp == 2) {
                #pragma unroll
                for (int i = NPRE; i < STAGES; i++) mbar_init(bfull + 8 * i, 1);
                #pragma unroll
                for (int i = 0; i < 4; i++) mbar_init(bfl + 8 * i, 1);
                #pragma unroll
                for (int i = 0; i < 4; i++) mbar_expect_tx(bfl + 8 * i, 2048);
                asm volatile("fence.mbarrier_init.release.cluster;" ::: "memory");
            } else {
                #pragma unroll
                for (int i = 0; i < 4; i++) mbar_init(bfr + 16 * i, 1);
                #pragma unroll
                for (int i = 0; i < 4; i++) mbar_expect_tx(bfr + 16 * i, 4096);
                asm volatile("fence.mbarrier_init.release.cluster;" ::: "memory");
            }
        }
    }
    asm volatile("bar.sync 1, %0;" :: "n"(NTHR) : "memory");
    asm volatile("barrier.cluster.arrive.relaxed.aligned;" ::: "memory");
    const int g = lane >> 2, tq = lane & 3;
    const int mi = lane >> 3, li = lane & 7;
    if (warp == 5) {
        const uint32_t ad0 = isv ? srecv + ((4 * (lane & 1) + ((lane >> 3) & 1)) * 4 + ((lane >> 1) & 3)) * 16 + (lane >> 4) * 8 : srecv + lane * 16;
        uint32_t rbase[8];
        #pragma unroll
        for (int rr = 0; rr < 8; rr++) rbase[rr] = mapa(sbase, (2 * rr + (lane >> 4) + j + 1) & 15) - sbase;
        const uint32_t la0 = sfrag + (isv * 8 + dh * 4 + nh) * 256 + (lane & 15) * 16;
        asm volatile("barrier.cluster.wait.aligned;" ::: "memory");
        #pragma unroll 1
        for (int hg = 0; hg < 4; hg++) {
            const uint32_t ad = ad0 + hg * 2048;
            mbar_wait_cluster(bfl + hg * 8);
            uint32_t o0, o1;
            if (!isv) {
                float4 x = lds4(ad), y = lds4(ad + 512), z = lds4(ad + 1024), v = lds4(ad + 1536);
                uint32_t k0 = pack2((x.x + y.x) + (z.x + v.x), (x.y + y.y) + (z.y + v.y));
                uint32_t k1 = pack2((x.z + y.z) + (z.z + v.z), (x.w + y.w) + (z.w + v.w));
                asm volatile("movmatrix.sync.aligned.m8n8.trans.b16 %0, %1;" : "=r"(o0) : "r"(k0));
                asm volatile("movmatrix.sync.aligned.m8n8.trans.b16 %0, %1;" : "=r"(o1) : "r"(k1));
            } else {
                float2 x = lds2(ad), y = lds2(ad + 512), z = lds2(ad + 1024), v = lds2(ad + 1536);
                float2 x2 = lds2(ad + 128), y2 = lds2(ad + 640), z2 = lds2(ad + 1152), v2 = lds2(ad + 1664);
                o0 = pack2((x.x + y.x) + (z.x + v.x), (x.y + y.y) + (z.y + v.y));
                o1 = pack2((x2.x + y2.x) + (z2.x + v2.x), (x2.y + y2.y) + (z2.y + v2.y));
            }
            const int sl = (lane & 15) * 2;
            const uint32_t w0 = __shfl_sync(~0u, o0, sl), w1 = __shfl_sync(~0u, o1, sl), w2 = __shfl_sync(~0u, o0, sl + 1), w3 = __shfl_sync(~0u, o1, sl + 1);
            const uint32_t la = la0 + hg * 4096, lb = bfr + hg * 16;
            #pragma unroll
            for (int rr = 0; rr < 8; rr++) st_async4(la + rbase[rr], w0, w1, w2, w3, lb + rbase[rr]);
        }
        return;
    }
    const int w = (warp - 1 - (warp > 5)) & 3;
    int n0 = w >> 1, n1 = 14;
    if (warp < 5) {
        const int dr = (j & 3) | (w << 2);
        const uint32_t ra = mapa(srecv + nh * 512 + lane * 16, dr), rb = mapa(bfl, dr);
        const uint32_t aoff = sbase + ((mi >> 1) * 8 + li) * 128 + (((2 * w + (mi & 1)) ^ li) << 4);
        const uint32_t boff = sproj + li * 128 + ((mi ^ li) << 4);
        unsigned long long m = ~qm, gm = qm << STAGES;
        int s = 0; unsigned par = 0;
        asm volatile("barrier.cluster.wait.aligned;" ::: "memory");
        mbar_wait(bproj, 0);
        #pragma unroll 1
        for (int hg = 0; hg < 4; hg++) {
            float acc[2][4] = {};
            #pragma unroll 1
            for (int i = 0; i < 8; i++) {
                uint32_t bb[8];
                ldsm4(boff + i * 1024, bb[0], bb[1], bb[2], bb[3]);
                ldsm4((boff ^ 64) + i * 1024, bb[4], bb[5], bb[6], bb[7]);
                if (gm & 1) mbar_wait(bempty + 8 * s, par ^ 1);
                mbar_wait(bfull + 8 * s, par);
                uint32_t a[4][4];
                #pragma unroll
                for (int ks = 0; ks < 4; ks++) ldsm4t(aoff + s * UB + ks * 2048, a[ks][0], a[ks][1], a[ks][2], a[ks][3]);
                #pragma unroll
                for (int ks = 0; ks < 4; ks++) mma16816(acc[ks & 1], a[ks][0], a[ks][1], a[ks][2], a[ks][3], bb[2 * ks], bb[2 * ks + 1]);
                if (i == 7)
                    st_async4(ra + hg * 2048, __float_as_uint(acc[0][0] + acc[1][0]), __float_as_uint(acc[0][1] + acc[1][1]),
                              __float_as_uint(acc[0][2] + acc[1][2]), __float_as_uint(acc[0][3] + acc[1][3]), rb + hg * 8);
                __syncwarp();
                if (lane == 0) mbar_arrive(bempty + 8 * s);
                const int dt = __ffs((unsigned)(m >> 1));
                m >>= dt; gm >>= dt; s += dt;
                if (s >= STAGES) { s -= STAGES; par ^= 1; }
            }
        }
        n0 += 14; n1 = 16;
    } else {
        asm volatile("barrier.cluster.wait.aligned;" ::: "memory");
    }
    const int rg = w & 1;
    const uint32_t qoff = sbase + (rg * 2 + (mi & 1)) * 2048 + li * 128;
    const uint32_t qx = (mi >> 1) ^ li;
    bf16* obase = pp.out + ((size_t)(grp * 512 + j * 8 + rg) * 16 + g) * DH + tq * 8;
    uint32_t kp[16], vp[16];
    unsigned long long m = qm;
    if (warp < 5) m = 3ull << 46;
    if (w & 2) m &= m - 1;
    #pragma unroll 1
    for (int n = n0; n < n1; n += 2) {
        const int t = __ffsll(m) - 1; m &= m - 1; m &= m - 1;
        const int r = (t * 26) >> 8, s = t - r * STAGES;
        const unsigned par = r & 1;
        const int hg = n >> 2;
        bf16* orow = obase + (size_t)(n * 2 + hg * 120) * 16 * DH;
        if (t >= STAGES) mbar_wait(bempty + 8 * s, par ^ 1);
        mbar_wait(bfull + 8 * s, par);
        uint32_t a[8][4];
        #pragma unroll
        for (int ks = 0; ks < 8; ks++) ldsm4(qoff + s * UB + (ks >> 2) * 1024 + ((qx ^ ((ks & 3) << 1)) << 4), a[ks][0], a[ks][1], a[ks][2], a[ks][3]);
        if ((n & 2) == 0 || n == n0) {
            mbar_wait_cluster(bfr + 16 * hg);
            #pragma unroll
            for (int i = 0; i < 8; i++)
                asm volatile("ld.shared.v2.u32 {%0,%1}, [%2];" : "=r"(kp[2 * i]), "=r"(kp[2 * i + 1]) : "r"(sfrag + hg * 4096 + i * 256 + lane * 8) : "memory");
            #pragma unroll
            for (int i = 0; i < 4; i++) { uint4 x = ldsu4(sfrag + hg * 4096 + 2048 + i * 512 + lane * 16); vp[4 * i] = x.x; vp[4 * i + 1] = x.y; vp[4 * i + 2] = x.z; vp[4 * i + 3] = x.w; }
        }
        float sc[4][4] = {};
        #pragma unroll
        for (int ks = 0; ks < 8; ks++) mma16816(sc[ks & 3], a[ks][0], a[ks][1], a[ks][2], a[ks][3], kp[2 * ks], kp[2 * ks + 1]);
        __syncwarp();
        if (lane < 2) mbar_arrive(bempty + 8 * s);
        const float scale = 0.08838834764831845f, l2e = 1.4426950408889634f;
        uint32_t u0 = pack2((sc[0][0] + sc[1][0]) + (sc[2][0] + sc[3][0]), (sc[0][2] + sc[1][2]) + (sc[2][2] + sc[3][2]));
        uint32_t u1 = pack2((sc[0][1] + sc[1][1]) + (sc[2][1] + sc[3][1]), (sc[0][3] + sc[1][3]) + (sc[2][3] + sc[3][3]));
        u0 = pack2(bf_lo(u0) * scale, bf_hi(u0) * scale);
        u1 = pack2(bf_lo(u1) * scale, bf_hi(u1) * scale);
        uint32_t mx = max2(u0, u1);
        {
            const uint32_t a1 = __shfl_xor_sync(~0u, mx, 1), a2 = __shfl_xor_sync(~0u, mx, 2), a3 = __shfl_xor_sync(~0u, mx, 3);
            mx = max2(max2(mx, a1), max2(a2, a3));
        }
        const float e0 = ex2((bf_lo(u0) - bf_lo(mx)) * l2e), e1 = ex2((bf_lo(u1) - bf_lo(mx)) * l2e);
        const float e2 = ex2((bf_hi(u0) - bf_hi(mx)) * l2e), e3 = ex2((bf_hi(u1) - bf_hi(mx)) * l2e);
        float s0 = e0 + e1, s1 = e2 + e3;
        {
            const float a1 = __shfl_xor_sync(~0u, s0, 1), b1 = __shfl_xor_sync(~0u, s1, 1);
            const float a2 = __shfl_xor_sync(~0u, s0, 2), b2 = __shfl_xor_sync(~0u, s1, 2);
            const float a3 = __shfl_xor_sync(~0u, s0, 3), b3 = __shfl_xor_sync(~0u, s1, 3);
            s0 = (s0 + a1) + (a2 + a3); s1 = (s1 + b1) + (b2 + b3);
        }
        const float r0 = rcpa(s0), r1 = rcpa(s1);
        const uint32_t pa0 = pack2(e0 * r0, e1 * r0), pa1 = pack2(e2 * r1, e3 * r1);
        #pragma unroll
        for (int J = 0; J < 4; J++) {
            float c[4][4];
            #pragma unroll
            for (int u = 0; u < 4; u++) mma1688z(c[u], pa0, pa1, vp[J * 4 + u]);
            *(uint4*)(orow + J * 32) = make_uint4(pack2(c[0][0], c[0][1]), pack2(c[1][0], c[1][1]), pack2(c[2][0], c[2][1]), pack2(c[3][0], c[3][1]));
            *(uint4*)(orow + 8 * DH + J * 32) = make_uint4(pack2(c[0][2], c[0][3]), pack2(c[1][2], c[1][3]), pack2(c[2][2], c[2][3]), pack2(c[3][2], c[3][3]));
        }
    }
}

typedef CUresult (*EncodeFn)(CUtensorMap*, CUtensorMapDataType, cuuint32_t, void*, const cuuint64_t*, const cuuint64_t*,
                             const cuuint32_t*, const cuuint32_t*, CUtensorMapInterleave, CUtensorMapSwizzle,
                             CUtensorMapL2promotion, CUtensorMapFloatOOBfill);

void make_rows_map(EncodeFn enc, CUtensorMap* m, void* p, int halves, int groups) {
    cuuint32_t es[4] = {1, 1, 1, 1};
    cuuint64_t d[4] = {64, 8, 2, 8192};
    cuuint64_t s[3] = {256, 128, 2048};
    cuuint32_t b[4] = {64, 8, (cuuint32_t)halves, (cuuint32_t)groups};
    enc(m, CU_TENSOR_MAP_DATA_TYPE_BFLOAT16, 4, p, d, s, b, es, CU_TENSOR_MAP_INTERLEAVE_NONE, CU_TENSOR_MAP_SWIZZLE_128B,
        CU_TENSOR_MAP_L2_PROMOTION_L2_128B, CU_TENSOR_MAP_FLOAT_OOB_FILL_NONE);
}
void make_proj_map(EncodeFn enc, CUtensorMap* m, void* p) {
    cuuint32_t es[3] = {1, 1, 1};
    cuuint64_t d[3] = {64, 8, 32};
    cuuint64_t s[2] = {4096, 128};
    cuuint32_t b[3] = {64, 8, 8};
    enc(m, CU_TENSOR_MAP_DATA_TYPE_BFLOAT16, 3, p, d, s, b, es, CU_TENSOR_MAP_INTERLEAVE_NONE, CU_TENSOR_MAP_SWIZZLE_128B,
        CU_TENSOR_MAP_L2_PROMOTION_L2_128B, CU_TENSOR_MAP_FLOAT_OOB_FILL_NONE);
}
Sched make_sched(const char* order, int w, int slack, int off, const int (&step)[NSEG]) {
    static const int next[NSEG] = {7, 12, 20, 30, 40, 44, 63};
    Sched s = {};
    for (int t = 0; t < NU; t++) if (order[t] == 'Q') s.qm |= 1ull << t;
    for (int i = 0; i < NSEG; i++) {
        const unsigned long long f = (unsigned long long)(step[i] / 2) | (unsigned long long)next[i] << 10;
        if (i < 4) s.seg0 |= f << (16 * i); else s.seg1 |= f << (16 * (i - 4));
    }
    s.off = off; s.slack = (unsigned short)slack; s.w = (unsigned short)w;
    return s;
}

void launch(void* const* d_in, void* d_out, const Sched& s0, const Sched& s1) {
    void* fn = nullptr;
    cudaDriverEntryPointQueryResult qr;
    cudaGetDriverEntryPoint("cuTensorMapEncodeTiled", &fn, cudaEnableDefault, &qr);
    EncodeFn enc = (EncodeFn)fn;
    CUtensorMap mq, mk, mv, me, mf;
    make_rows_map(enc, &mq, d_in[0], 2, 4);
    make_rows_map(enc, &mk, d_in[1], 1, 8);
    make_rows_map(enc, &mv, d_in[2], 1, 8);
    make_proj_map(enc, &me, d_in[3]);
    make_proj_map(enc, &mf, d_in[4]);
    Params pp;
    pp.kv[0] = (const char*)d_in[1]; pp.kv[1] = (const char*)d_in[2];
    pp.out = (bf16*)d_out;
    pp.c[0] = s0; pp.c[1] = s1;
    cudaFuncSetAttribute(linformer_kernel, cudaFuncAttributeMaxDynamicSharedMemorySize, SMEM_BYTES);
    cudaFuncSetAttribute(linformer_kernel, cudaFuncAttributeNonPortableClusterSizeAllowed, 1);
    cudaLaunchConfig_t cfg = {};
    cfg.gridDim = dim3(128);
    cfg.blockDim = dim3(NTHR);
    cfg.dynamicSmemBytes = SMEM_BYTES;
    cfg.stream = cudaStreamPerThread;
    cudaLaunchAttribute at[2];
    at[0].id = cudaLaunchAttributeClusterDimension;
    at[0].val.clusterDim.x = 16; at[0].val.clusterDim.y = 1; at[0].val.clusterDim.z = 1;
    at[1].id = cudaLaunchAttributeClusterSchedulingPolicyPreference;
    at[1].val.clusterSchedulingPolicyPreference = cudaClusterSchedulingPolicyLoadBalancing;
    cfg.attrs = at; cfg.numAttrs = 2;
    cudaLaunchKernelEx(&cfg, linformer_kernel, pp, mk, mv, me, mf, mq);
}

}

extern "C" void kernel_launch(void* const* d_in, const int* in_sizes, int n_in, void* d_out, int out_size) {
    (void)in_sizes; (void)n_in; (void)out_size;
    const char* order = "KKKKKKKKKQKKQKKQKKQKKQKKQKKQKKQKKQKKQKKQKKKQQQQQ";
    lf::launch(d_in, d_out,
               lf::make_sched(order, 7, 300, 600, {334, 334, 332, 334, 336, 336, 336}),
               lf::make_sched(order, 8, 300, 720, {328, 306, 292, 298, 302, 292, 282}));
}
```

```cpp
#include <cuda_runtime.h>
#include <cuda_bf16.h>
#include <cuda.h>
#include <stdint.h>

namespace lf {

typedef __nv_bfloat16 bf16;

constexpr int DH = 128;
constexpr int NU = 48;
constexpr int UB = 8192;
constexpr int STAGES = 10;
constexpr int NTHR = 320;
constexpr int NPRE = 4;
constexpr int SMEM_BYTES = STAGES * UB + 8192 + 8192 + 16384 + 1024;

constexpr int NSEG = 7;

struct Sched { unsigned long long qm, seg0, seg1; int off; unsigned short slack, w; };
struct Params {
    const char* kv[2];
    bf16* out;
    Sched c[2];
};

__device__ __forceinline__ uint32_t smem_u32(const void* p) { return (uint32_t)__cvta_generic_to_shared(p); }
__device__ __forceinline__ void mbar_init(uint32_t bar, uint32_t cnt) { asm volatile("mbarrier.init.shared::cta.b64 [%0], %1;" :: "r"(bar), "r"(cnt) : "memory"); }
__device__ __forceinline__ void mbar_expect_tx(uint32_t bar, uint32_t bytes) { asm volatile("mbarrier.arrive.expect_tx.shared::cta.b64 _, [%0], %1;" :: "r"(bar), "r"(bytes) : "memory"); }
__device__ __forceinline__ void mbar_arrive(uint32_t bar) { asm volatile("mbarrier.arrive.shared::cta.b64 _, [%0];" :: "r"(bar) : "memory"); }
__device__ __forceinline__ void mbar_wait(uint32_t bar, uint32_t parity) {
    uint32_t done; int it = 0;
    do {
        asm volatile("{\n.reg .pred p;\nmbarrier.try_wait.parity.shared::cta.b64 p, [%1], %2;\nselp.u32 %0, 1, 0, p;\n}" : "=r"(done) : "r"(bar), "r"(parity) : "memory");
        if (++it > (1 << 22)) __trap();
    } while (!done);
}
__device__ __forceinline__ void mbar_wait_cluster(uint32_t bar) {
    uint32_t done; int it = 0;
    do {
        asm volatile("{\n.reg .pred p;\nmbarrier.try_wait.parity.acquire.cluster.shared::cta.b64 p, [%1], 0;\nselp.u32 %0, 1, 0, p;\n}" : "=r"(done) : "r"(bar) : "memory");
        if (++it > (1 << 22)) __trap();
    } while (!done);
}
__device__ __forceinline__ uint32_t mbar_test(uint32_t bar, uint32_t par) {
    uint32_t d;
    asm volatile("{\n.reg .pred p;\nmbarrier.test_wait.parity.shared::cta.b64 p, [%1], %2;\nselp.u32 %0, 1, 0, p;\n}" : "=r"(d) : "r"(bar), "r"(par) : "memory");
    return d;
}
__device__ __forceinline__ void tma_load4(uint32_t dst, const CUtensorMap* m, int c2, int c3, uint32_t bar, uint64_t pol) {
    asm volatile("cp.async.bulk.tensor.4d.shared::cluster.global.mbarrier::complete_tx::bytes.L2::cache_hint [%0], [%1, {%3, %3, %4, %5}], [%2], %6;"
                 :: "r"(dst), "l"(m), "r"(bar), "r"(0), "r"(c2), "r"(c3), "l"(pol) : "memory");
}
__device__ __forceinline__ void tma_load3(uint32_t dst, const CUtensorMap* m, int blk, uint32_t bar) {
    asm volatile("cp.async.bulk.tensor.3d.shared::cluster.global.mbarrier::complete_tx::bytes [%0], [%1, {%3, %3, %4}], [%2];"
                 :: "r"(dst), "l"(m), "r"(bar), "r"(0), "r"(blk) : "memory");
}
__device__ __forceinline__ void ldsm4(uint32_t a, uint32_t& r0, uint32_t& r1, uint32_t& r2, uint32_t& r3) {
    asm volatile("ldmatrix.sync.aligned.m8n8.x4.shared.b16 {%0,%1,%2,%3}, [%4];" : "=r"(r0), "=r"(r1), "=r"(r2), "=r"(r3) : "r"(a) : "memory");
}
__device__ __forceinline__ void ldsm4t(uint32_t a, uint32_t& r0, uint32_t& r1, uint32_t& r2, uint32_t& r3) {
    asm volatile("ldmatrix.sync.aligned.m8n8.x4.trans.shared.b16 {%0,%1,%2,%3}, [%4];" : "=r"(r0), "=r"(r1), "=r"(r2), "=r"(r3) : "r"(a) : "memory");
}
__device__ __forceinline__ void mma16816(float* c, uint32_t a0, uint32_t a1, uint32_t a2, uint32_t a3, uint32_t b0, uint32_t b1) {
    asm volatile("mma.sync.aligned.m16n8k16.row.col.f32.bf16.bf16.f32 {%0,%1,%2,%3}, {%4,%5,%6,%7}, {%8,%9}, {%0,%1,%2,%3};"
                 : "+f"(c[0]), "+f"(c[1]), "+f"(c[2]), "+f"(c[3]) : "r"(a0), "r"(a1), "r"(a2), "r"(a3), "r"(b0), "r"(b1));
}
__device__ __forceinline__ void mma1688z(float* c, uint32_t a0, uint32_t a1, uint32_t b0) {
    asm volatile("mma.sync.aligned.m16n8k8.row.col.f32.bf16.bf16.f32 {%0,%1,%2,%3}, {%4,%5}, {%6}, {%7,%7,%7,%7};"
                 : "=f"(c[0]), "=f"(c[1]), "=f"(c[2]), "=f"(c[3]) : "r"(a0), "r"(a1), "r"(b0), "f"(0.f));
}
__device__ __forceinline__ uint32_t pack2(float lo, float hi) { uint32_t r; asm("cvt.rn.bf16x2.f32 %0, %1, %2;" : "=r"(r) : "f"(hi), "f"(lo)); return r; }
__device__ __forceinline__ float ex2(float x) { float y; asm("ex2.approx.ftz.f32 %0, %1;" : "=f"(y) : "f"(x)); return y; }
__device__ __forceinline__ uint32_t max2(uint32_t a, uint32_t b) { uint32_t r; asm("max.NaN.bf16x2 %0, %1, %2;" : "=r"(r) : "r"(a), "r"(b)); return r; }
__device__ __forceinline__ float bf_lo(uint32_t u) { return __uint_as_float(u << 16); }
__device__ __forceinline__ float bf_hi(uint32_t u) { return __uint_as_float(u & 0xffff0000u); }
__device__ __forceinline__ float rcpa(float x) { float y; asm("rcp.approx.ftz.f32 %0, %1;" : "=f"(y) : "f"(x)); return y; }
__device__ __forceinline__ uint32_t mapa(uint32_t a, int r) { uint32_t o; asm("mapa.shared::cluster.u32 %0, %1, %2;" : "=r"(o) : "r"(a), "r"(r)); return o; }
__device__ __forceinline__ bool elect_one() { uint32_t p; asm volatile("{\n.reg .pred P;\nelect.sync _|P, 0xffffffff;\nselp.u32 %0, 1, 0, P;\n}" : "=r"(p)); return p; }
__device__ __forceinline__ void st_async4(uint32_t a, uint32_t x, uint32_t y, uint32_t z, uint32_t w, uint32_t b) {
    asm volatile("st.async.weak.shared::cluster.mbarrier::complete_tx::bytes.v4.b32 [%0], {%1,%2,%3,%4}, [%5];" :: "r"(a), "r"(x), "r"(y), "r"(z), "r"(w), "r"(b) : "memory");
}
__device__ __forceinline__ float4 lds4(uint32_t a) { float4 x; asm volatile("ld.shared.v4.f32 {%0,%1,%2,%3}, [%4];" : "=f"(x.x), "=f"(x.y), "=f"(x.z), "=f"(x.w) : "r"(a) : "memory"); return x; }
__device__ __forceinline__ float2 lds2(uint32_t a) { float2 x; asm volatile("ld.shared.v2.f32 {%0,%1}, [%2];" : "=f"(x.x), "=f"(x.y) : "r"(a) : "memory"); return x; }
__device__ __forceinline__ uint4 ldsu4(uint32_t a) { uint4 x; asm volatile("ld.shared.v4.u32 {%0,%1,%2,%3}, [%4];" : "=r"(x.x), "=r"(x.y), "=r"(x.z), "=r"(x.w) : "r"(a) : "memory"); return x; }

__device__ __forceinline__ void stg4(void* p, uint4 v) {
    asm volatile("st.global.v4.u32 [%0], {%1,%2,%3,%4};" :: "l"(p), "r"(v.x), "r"(v.y), "r"(v.z), "r"(v.w) : "memory");
}
__device__ __forceinline__ uint4 shfl_xor4(uint4 v, int m) {
    return make_uint4(__shfl_xor_sync(~0u, v.x, m), __shfl_xor_sync(~0u, v.y, m), __shfl_xor_sync(~0u, v.z, m), __shfl_xor_sync(~0u, v.w, m));
}

__global__ void __launch_bounds__(NTHR, 2)
linformer_kernel(const __grid_constant__ Params pp,
                 const __grid_constant__ CUtensorMap mk, const __grid_constant__ CUtensorMap mv,
                 const __grid_constant__ CUtensorMap me, const __grid_constant__ CUtensorMap mf,
                 const __grid_constant__ CUtensorMap mq) {
    const uint64_t pol = 0x12F0000000000000ull;
    const unsigned b = blockIdx.x;
    const int tid = threadIdx.x, lane = tid & 31;
    if (tid == 32)
        asm volatile("cp.async.bulk.prefetch.L2.global.L2::cache_hint [%0], %1, %2;"
                     :: "l"(pp.kv[b & 1] + (((b >> 4) << 21) | ((b & 12) << 15) | ((b & 2) << 14))), "r"(NPRE * UB), "l"(pol) : "memory");
    const int grp = b >> 4, j = b & 15;
    const int isv = j & 1, dh = (j >> 1) & 1, nh = j >> 2;
    const int kvr = grp * 1024 + nh * 64;
    extern __shared__ __align__(1024) char smem_raw[];
    const uint32_t sbase = smem_u32(smem_raw);
    const uint32_t sproj = sbase + STAGES * UB, srecv = sproj + 8192, sfrag = srecv + 8192;
    const uint32_t bfull = sfrag + 16384, bempty = bfull + 8 * STAGES, bproj = bempty + 8 * STAGES, bfl = bproj + 8, bfr = bfl + 32;
    const int warp = __shfl_sync(~0u, tid >> 5, 0);
    const CUtensorMap* mkv = isv ? &mv : &mk;
    const bool el = elect_one();
    const int cls = grp == 7;
    if (warp == 0) {
        unsigned tz; asm volatile("mov.u32 %0, %%globaltimer_lo;" : "=r"(tz));
        if (el) {
            #pragma unroll
            for (int p = 0; p < NPRE; p++) mbar_init(bfull + 8 * p, 1);
            mbar_init(bproj, 1);
            mbar_expect_tx(bproj, 8192);
            tma_load3(sproj, isv ? &mf : &me, nh * 8, bproj);
            #pragma unroll
            for (int p = 0; p < NPRE; p++) {
                mbar_expect_tx(bfull + 8 * p, UB);
                tma_load4(sbase + p * UB, mkv, dh, kvr + p * 8, bfull + 8 * p, pol);
            }
        }
        asm volatile("bar.arrive 2, 128;" ::: "memory");
        if (el) asm volatile("prefetch.tensormap [%0];" :: "l"(&mq) : "memory");
        const Sched& sc = pp.c[cls];
        unsigned long long m = sc.qm >> NPRE;
        unsigned long long sg0 = sc.seg0, sg1 = sc.seg1;
        unsigned dl = tz + sc.off;
        const unsigned slack = sc.slack;
        int ck = kvr + NPRE * 8, cq = grp * 1024 + j * 16;
        int s = NPRE, su = NPRE - sc.w + STAGES;
        unsigned ph = 1, phu = 1;
        if (su >= STAGES) { su -= STAGES; phu = 0; }
        asm volatile("bar.sync 1, %0;" :: "n"(NTHR) : "memory");
        asm volatile("barrier.cluster.arrive.relaxed.aligned;" ::: "memory");
        #pragma unroll 1
        for (int t = NPRE; t < NU; t++) {
            const bool isq = m & 1; m >>= 1;
            const CUtensorMap* mp = isq ? &mq : mkv;
            const int c2 = isq ? 0 : dh, c3 = isq ? cq : ck;
            int it = 0;
            unsigned now;
            while (true) {
                const uint32_t slot_free = mbar_test(bempty + 8 * s, ph), landed = mbar_test(bfull + 8 * su, phu);
                asm volatile("mov.u32 %0, %%globaltimer_lo;" : "=r"(now));
                if (slot_free && landed && (int)(now - dl) >= 0) break;
                if (++it > (1 << 22)) __trap();
            }
            if (el) {
                mbar_expect_tx(bfull + 8 * s, UB);
                tma_load4(sbase + s * UB, mp, c2, c3, bfull + 8 * s, pol);
            }
            if (isq) { cq += 4; if ((cq & 15) == 0) cq += 240; } else { ck += 8; if ((ck & 63) == 0) ck += 192; }
            if (t == (int)(((unsigned)sg0 >> 10) & 63)) { sg0 = (sg0 >> 16) | (sg1 << 48); sg1 >>= 16; }
            if ((int)(now - slack - dl) > 0) dl = now - slack;
            dl += ((unsigned)sg0 & 1023) * 2;
            if (++s == STAGES) { s = 0; ph ^= 1; }
            if (++su == STAGES) { su = 0; phu ^= 1; }
        }
        asm volatile("barrier.cluster.wait.aligned;" ::: "memory");
        return;
    }
    const unsigned long long qm = pp.c[cls].qm;
    if (warp <= 3) {
        asm volatile("bar.sync 2, 128;" ::: "memory");
        if (el) {
            if (warp == 1) {
                #pragma unroll
                for (int i = 0; i < STAGES; i++) mbar_init(bempty + 8 * i, 4);
            } else if (warp == 2) {
                #pragma unroll
                for (int i = NPRE; i < STAGES; i++) mbar_init(bfull + 8 * i, 1);
                #pragma unroll
                for (int i = 0; i < 4; i++) mbar_init(bfl + 8 * i, 1);
                #pragma unroll
                for (int i = 0; i < 4; i++) mbar_expect_tx(bfl + 8 * i, 2048);
                asm volatile("fence.mbarrier_init.release.cluster;" ::: "memory");
            } else {
                #pragma unroll
                for (int i = 0; i < 4; i++) mbar_init(bfr + 16 * i, 1);
                #pragma unroll
                for (int i = 0; i < 4; i++) mbar_expect_tx(bfr + 16 * i, 4096);
                asm volatile("fence.mbarrier_init.release.cluster;" ::: "memory");
            }
        }
    }
    asm volatile("bar.sync 1, %0;" :: "n"(NTHR) : "memory");
    asm volatile("barrier.cluster.arrive.relaxed.aligned;" ::: "memory");
    const int g = lane >> 2;
    const int mi = lane >> 3, li = lane & 7;
    if (warp == 5) {
        const uint32_t ad0 = isv ? srecv + ((4 * (lane & 1) + ((lane >> 3) & 1)) * 4 + ((lane >> 1) & 3)) * 16 + (lane >> 4) * 8 : srecv + lane * 16;
        uint32_t rbase[8];
        #pragma unroll
        for (int rr = 0; rr < 8; rr++) rbase[rr] = mapa(sbase, (2 * rr + (lane >> 4) + j + 1) & 15) - sbase;
        const uint32_t la0 = sfrag + (isv * 8 + dh * 4 + nh) * 256 + (lane & 15) * 16;
        asm volatile("barrier.cluster.wait.aligned;" ::: "memory");
        #pragma unroll 1
        for (int hg = 0; hg < 4; hg++) {
            const uint32_t ad = ad0 + hg * 2048;
            mbar_wait_cluster(bfl + hg * 8);
            uint32_t o0, o1;
            if (!isv) {
                float4 x = lds4(ad), y = lds4(ad + 512), z = lds4(ad + 1024), v = lds4(ad + 1536);
                uint32_t k0 = pack2((x.x + y.x) + (z.x + v.x), (x.y + y.y) + (z.y + v.y));
                uint32_t k1 = pack2((x.z + y.z) + (z.z + v.z), (x.w + y.w) + (z.w + v.w));
                asm volatile("movmatrix.sync.aligned.m8n8.trans.b16 %0, %1;" : "=r"(o0) : "r"(k0));
                asm volatile("movmatrix.sync.aligned.m8n8.trans.b16 %0, %1;" : "=r"(o1) : "r"(k1));
            } else {
                float2 x = lds2(ad), y = lds2(ad + 512), z = lds2(ad + 1024), v = lds2(ad + 1536);
                float2 x2 = lds2(ad + 128), y2 = lds2(ad + 640), z2 = lds2(ad + 1152), v2 = lds2(ad + 1664);
                o0 = pack2((x.x + y.x) + (z.x + v.x), (x.y + y.y) + (z.y + v.y));
                o1 = pack2((x2.x + y2.x) + (z2.x + v2.x), (x2.y + y2.y) + (z2.y + v2.y));
            }
            const int sl = (lane & 15) * 2;
            const uint32_t w0 = __shfl_sync(~0u, o0, sl), w1 = __shfl_sync(~0u, o1, sl), w2 = __shfl_sync(~0u, o0, sl + 1), w3 = __shfl_sync(~0u, o1, sl + 1);
            const uint32_t la = la0 + hg * 4096, lb = bfr + hg * 16;
            #pragma unroll
            for (int rr = 0; rr < 8; rr++) st_async4(la + rbase[rr], w0, w1, w2, w3, lb + rbase[rr]);
        }
        return;
    }
    const int w = (warp - 1 - (warp > 5)) & 3;
    int n0 = w >> 1, n1 = 14;
    if (warp < 5) {
        const int dr = (j & 3) | (w << 2);
        const uint32_t ra = mapa(srecv + nh * 512 + lane * 16, dr), rb = mapa(bfl, dr);
        const uint32_t aoff = sbase + ((mi >> 1) * 8 + li) * 128 + (((2 * w + (mi & 1)) ^ li) << 4);
        const uint32_t boff = sproj + li * 128 + ((mi ^ li) << 4);
        unsigned long long m = ~qm, gm = qm << STAGES;
        int s = 0; unsigned par = 0;
        asm volatile("barrier.cluster.wait.aligned;" ::: "memory");
        mbar_wait(bproj, 0);
        #pragma unroll 1
        for (int hg = 0; hg < 4; hg++) {
            float acc[2][4] = {};
            #pragma unroll 1
            for (int i = 0; i < 8; i++) {
                uint32_t bb[8];
                ldsm4(boff + i * 1024, bb[0], bb[1], bb[2], bb[3]);
                ldsm4((boff ^ 64) + i * 1024, bb[4], bb[5], bb[6], bb[7]);
                if (gm & 1) mbar_wait(bempty + 8 * s, par ^ 1);
                mbar_wait(bfull + 8 * s, par);
                uint32_t a[4][4];
                #pragma unroll
                for (int ks = 0; ks < 4; ks++) ldsm4t(aoff + s * UB + ks * 2048, a[ks][0], a[ks][1], a[ks][2], a[ks][3]);
                #pragma unroll
                for (int ks = 0; ks < 4; ks++) mma16816(acc[ks & 1], a[ks][0], a[ks][1], a[ks][2], a[ks][3], bb[2 * ks], bb[2 * ks + 1]);
                if (i == 7)
                    st_async4(ra + hg * 2048, __float_as_uint(acc[0][0] + acc[1][0]), __float_as_uint(acc[0][1] + acc[1][1]),
                              __float_as_uint(acc[0][2] + acc[1][2]), __float_as_uint(acc[0][3] + acc[1][3]), rb + hg * 8);
                __syncwarp();
                if (lane == 0) mbar_arrive(bempty + 8 * s);
                const int dt = __ffs((unsigned)(m >> 1));
                m >>= dt; gm >>= dt; s += dt;
                if (s >= STAGES) { s -= STAGES; par ^= 1; }
            }
        }
        n0 += 14; n1 = 16;
    } else {
        asm volatile("barrier.cluster.wait.aligned;" ::: "memory");
    }
    const int rg = w & 1;
    const uint32_t qoff = sbase + (rg * 2 + (mi & 1)) * 2048 + li * 128;
    const uint32_t qx = (mi >> 1) ^ li;
    bf16* obase = pp.out + ((size_t)(grp * 512 + j * 8 + rg) * 16 + (g & 6)) * DH + (lane & 7) * 8;
    uint32_t kp[16], vp[16];
    unsigned long long m = qm;
    if (warp < 5) m = 3ull << 46;
    if (w & 2) m &= m - 1;
    #pragma unroll 1
    for (int n = n0; n < n1; n += 2) {
        const int t = __ffsll(m) - 1; m &= m - 1; m &= m - 1;
        const int r = (t * 26) >> 8, s = t - r * STAGES;
        const unsigned par = r & 1;
        const int hg = n >> 2;
        bf16* orow = obase + (size_t)(n * 2 + hg * 120) * 16 * DH;
        if (t >= STAGES) mbar_wait(bempty + 8 * s, par ^ 1);
        mbar_wait(bfull + 8 * s, par);
        uint32_t a[8][4];
        #pragma unroll
        for (int ks = 0; ks < 8; ks++) ldsm4(qoff + s * UB + (ks >> 2) * 1024 + ((qx ^ ((ks & 3) << 1)) << 4), a[ks][0], a[ks][1], a[ks][2], a[ks][3]);
        if ((n & 2) == 0 || n == n0) {
            mbar_wait_cluster(bfr + 16 * hg);
            #pragma unroll
            for (int i = 0; i < 8; i++)
                asm volatile("ld.shared.v2.u32 {%0,%1}, [%2];" : "=r"(kp[2 * i]), "=r"(kp[2 * i + 1]) : "r"(sfrag + hg * 4096 + i * 256 + lane * 8) : "memory");
            #pragma unroll
            for (int i = 0; i < 4; i++) { uint4 x = ldsu4(sfrag + hg * 4096 + 2048 + i * 512 + lane * 16); vp[4 * i] = x.x; vp[4 * i + 1] = x.y; vp[4 * i + 2] = x.z; vp[4 * i + 3] = x.w; }
        }
        float sc[4][4] = {};
        #pragma unroll
        for (int ks = 0; ks < 8; ks++) mma16816(sc[ks & 3], a[ks][0], a[ks][1], a[ks][2], a[ks][3], kp[2 * ks], kp[2 * ks + 1]);
        __syncwarp();
        if (lane < 2) mbar_arrive(bempty + 8 * s);
        const float scale = 0.08838834764831845f, l2e = 1.4426950408889634f;
        uint32_t u0 = pack2((sc[0][0] + sc[1][0]) + (sc[2][0] + sc[3][0]), (sc[0][2] + sc[1][2]) + (sc[2][2] + sc[3][2]));
        uint32_t u1 = pack2((sc[0][1] + sc[1][1]) + (sc[2][1] + sc[3][1]), (sc[0][3] + sc[1][3]) + (sc[2][3] + sc[3][3]));
        u0 = pack2(bf_lo(u0) * scale, bf_hi(u0) * scale);
        u1 = pack2(bf_lo(u1) * scale, bf_hi(u1) * scale);
        uint32_t mx = max2(u0, u1);
        {
            const uint32_t a1 = __shfl_xor_sync(~0u, mx, 1), a2 = __shfl_xor_sync(~0u, mx, 2), a3 = __shfl_xor_sync(~0u, mx, 3);
            mx = max2(max2(mx, a1), max2(a2, a3));
        }
        const float e0 = ex2((bf_lo(u0) - bf_lo(mx)) * l2e), e1 = ex2((bf_lo(u1) - bf_lo(mx)) * l2e);
        const float e2 = ex2((bf_hi(u0) - bf_hi(mx)) * l2e), e3 = ex2((bf_hi(u1) - bf_hi(mx)) * l2e);
        float s0 = e0 + e1, s1 = e2 + e3;
        {
            const float a1 = __shfl_xor_sync(~0u, s0, 1), b1 = __shfl_xor_sync(~0u, s1, 1);
            const float a2 = __shfl_xor_sync(~0u, s0, 2), b2 = __shfl_xor_sync(~0u, s1, 2);
            const float a3 = __shfl_xor_sync(~0u, s0, 3), b3 = __shfl_xor_sync(~0u, s1, 3);
            s0 = (s0 + a1) + (a2 + a3); s1 = (s1 + b1) + (b2 + b3);
        }
        const float r0 = rcpa(s0), r1 = rcpa(s1);
        const uint32_t pa0 = pack2(e0 * r0, e1 * r0), pa1 = pack2(e2 * r1, e3 * r1);
        #pragma unroll
        for (int H = 0; H < 2; H++) {
            uint4 lo[2], hi[2];
            #pragma unroll
            for (int J = 0; J < 2; J++) {
                float c[4][4];
                #pragma unroll
                for (int u = 0; u < 4; u++) mma1688z(c[u], pa0, pa1, vp[H * 8 + J * 4 + u]);
                lo[J] = make_uint4(pack2(c[0][0], c[0][1]), pack2(c[1][0], c[1][1]), pack2(c[2][0], c[2][1]), pack2(c[3][0], c[3][1]));
                hi[J] = make_uint4(pack2(c[0][2], c[0][3]), pack2(c[1][2], c[1][3]), pack2(c[2][2], c[2][3]), pack2(c[3][2], c[3][3]));
            }
            const bool od = g & 1;
            const uint4 xl = shfl_xor4(od ? lo[0] : lo[1], 4), xh = shfl_xor4(od ? hi[0] : hi[1], 4);
            bf16* pe = orow + H * 64;
            stg4(pe, od ? xl : lo[0]);
            stg4(pe + DH, od ? lo[1] : xl);
            stg4(pe + 8 * DH, od ? xh : hi[0]);
            stg4(pe + 9 * DH, od ? hi[1] : xh);
        }
    }
}

typedef CUresult (*EncodeFn)(CUtensorMap*, CUtensorMapDataType, cuuint32_t, void*, const cuuint64_t*, const cuuint64_t*,
                             const cuuint32_t*, const cuuint32_t*, CUtensorMapInterleave, CUtensorMapSwizzle,
                             CUtensorMapL2promotion, CUtensorMapFloatOOBfill);

void make_rows_map(EncodeFn enc, CUtensorMap* m, void* p, int halves, int groups) {
    cuuint32_t es[4] = {1, 1, 1, 1};
    cuuint64_t d[4] = {64, 8, 2, 8192};
    cuuint64_t s[3] = {256, 128, 2048};
    cuuint32_t b[4] = {64, 8, (cuuint32_t)halves, (cuuint32_t)groups};
    enc(m, CU_TENSOR_MAP_DATA_TYPE_BFLOAT16, 4, p, d, s, b, es, CU_TENSOR_MAP_INTERLEAVE_NONE, CU_TENSOR_MAP_SWIZZLE_128B,
        CU_TENSOR_MAP_L2_PROMOTION_L2_128B, CU_TENSOR_MAP_FLOAT_OOB_FILL_NONE);
}
void make_proj_map(EncodeFn enc, CUtensorMap* m, void* p) {
    cuuint32_t es[3] = {1, 1, 1};
    cuuint64_t d[3] = {64, 8, 32};
    cuuint64_t s[2] = {4096, 128};
    cuuint32_t b[3] = {64, 8, 8};
    enc(m, CU_TENSOR_MAP_DATA_TYPE_BFLOAT16, 3, p, d, s, b, es, CU_TENSOR_MAP_INTERLEAVE_NONE, CU_TENSOR_MAP_SWIZZLE_128B,
        CU_TENSOR_MAP_L2_PROMOTION_L2_128B, CU_TENSOR_MAP_FLOAT_OOB_FILL_NONE);
}
Sched make_sched(const char* order, int w, int slack, int off, const int (&step)[NSEG]) {
    static const int next[NSEG] = {7, 12, 20, 30, 40, 44, 63};
    Sched s = {};
    for (int t = 0; t < NU; t++) if (order[t] == 'Q') s.qm |= 1ull << t;
    for (int i = 0; i < NSEG; i++) {
        const unsigned long long f = (unsigned long long)(step[i] / 2) | (unsigned long long)next[i] << 10;
        if (i < 4) s.seg0 |= f << (16 * i); else s.seg1 |= f << (16 * (i - 4));
    }
    s.off = off; s.slack = (unsigned short)slack; s.w = (unsigned short)w;
    return s;
}

void launch(void* const* d_in, void* d_out, const Sched& s0, const Sched& s1) {
    void* fn = nullptr;
    cudaDriverEntryPointQueryResult qr;
    cudaGetDriverEntryPoint("cuTensorMapEncodeTiled", &fn, cudaEnableDefault, &qr);
    EncodeFn enc = (EncodeFn)fn;
    CUtensorMap mq, mk, mv, me, mf;
    make_rows_map(enc, &mq, d_in[0], 2, 4);
    make_rows_map(enc, &mk, d_in[1], 1, 8);
    make_rows_map(enc, &mv, d_in[2], 1, 8);
    make_proj_map(enc, &me, d_in[3]);
    make_proj_map(enc, &mf, d_in[4]);
    Params pp;
    pp.kv[0] = (const char*)d_in[1]; pp.kv[1] = (const char*)d_in[2];
    pp.out = (bf16*)d_out;
    pp.c[0] = s0; pp.c[1] = s1;
    cudaFuncSetAttribute(linformer_kernel, cudaFuncAttributeMaxDynamicSharedMemorySize, SMEM_BYTES);
    cudaFuncSetAttribute(linformer_kernel, cudaFuncAttributeNonPortableClusterSizeAllowed, 1);
    cudaLaunchConfig_t cfg = {};
    cfg.gridDim = dim3(128);
    cfg.blockDim = dim3(NTHR);
    cfg.dynamicSmemBytes = SMEM_BYTES;
    cfg.stream = cudaStreamPerThread;
    cudaLaunchAttribute at[2];
    at[0].id = cudaLaunchAttributeClusterDimension;
    at[0].val.clusterDim.x = 16; at[0].val.clusterDim.y = 1; at[0].val.clusterDim.z = 1;
    at[1].id = cudaLaunchAttributeClusterSchedulingPolicyPreference;
    at[1].val.clusterSchedulingPolicyPreference = cudaClusterSchedulingPolicyLoadBalancing;
    cfg.attrs = at; cfg.numAttrs = 2;
    cudaLaunchKernelEx(&cfg, linformer_kernel, pp, mk, mv, me, mf, mq);
}

}

extern "C" void kernel_launch(void* const* d_in, const int* in_sizes, int n_in, void* d_out, int out_size) {
    (void)in_sizes; (void)n_in; (void)out_size;
    const char* order = "KKKKKKKKKQKKQKKQKKQKKQKKQKKQKKQKKQKKQKKQKKKQQQQQ";
    lf::launch(d_in, d_out,
               lf::make_sched(order, 8, 300, 680, {334, 334, 332, 334, 336, 336, 330}),
               lf::make_sched(order, 9, 300, 770, {328, 302, 288, 294, 298, 292, 282}));
}
```

```cpp
#include <cuda_runtime.h>
#include <cuda_bf16.h>
#include <cuda.h>
#include <stdint.h>

namespace lf {

typedef __nv_bfloat16 bf16;

constexpr int DH = 128;
constexpr int NU = 48;
constexpr int UB = 8192;
constexpr int STAGES = 10;
constexpr int NTHR = 320;
constexpr int NPRE = 4;
constexpr int SMEM_BYTES = STAGES * UB + 8192 + 8192 + 16384 + 1024;

constexpr int NSEG = 7;

struct Sched { unsigned long long qm, seg0, seg1; int off; unsigned short slack, w; };
struct Params {
    const char* kv[2];
    bf16* out;
    Sched c[2];
};

__device__ __forceinline__ uint32_t smem_u32(const void* p) { return (uint32_t)__cvta_generic_to_shared(p); }
__device__ __forceinline__ void mbar_init(uint32_t bar, uint32_t cnt) { asm volatile("mbarrier.init.shared::cta.b64 [%0], %1;" :: "r"(bar), "r"(cnt) : "memory"); }
__device__ __forceinline__ void mbar_expect_tx(uint32_t bar, uint32_t bytes) { asm volatile("mbarrier.arrive.expect_tx.shared::cta.b64 _, [%0], %1;" :: "r"(bar), "r"(bytes) : "memory"); }
__device__ __forceinline__ void mbar_arrive(uint32_t bar) { asm volatile("mbarrier.arrive.shared::cta.b64 _, [%0];" :: "r"(bar) : "memory"); }
__device__ __forceinline__ void mbar_wait(uint32_t bar, uint32_t parity) {
    uint32_t done; int it = 0;
    do {
        asm volatile("{\n.reg .pred p;\nmbarrier.try_wait.parity.shared::cta.b64 p, [%1], %2;\nselp.u32 %0, 1, 0, p;\n}" : "=r"(done) : "r"(bar), "r"(parity) : "memory");
        if (++it > (1 << 22)) __trap();
    } while (!done);
}
__device__ __forceinline__ void mbar_wait_cluster(uint32_t bar) {
    uint32_t done; int it = 0;
    do {
        asm volatile("{\n.reg .pred p;\nmbarrier.try_wait.parity.acquire.cluster.shared::cta.b64 p, [%1], 0;\nselp.u32 %0, 1, 0, p;\n}" : "=r"(done) : "r"(bar) : "memory");
        if (++it > (1 << 22)) __trap();
    } while (!done);
}
__device__ __forceinline__ uint32_t mbar_test(uint32_t bar, uint32_t par) {
    uint32_t d;
    asm volatile("{\n.reg .pred p;\nmbarrier.test_wait.parity.shared::cta.b64 p, [%1], %2;\nselp.u32 %0, 1, 0, p;\n}" : "=r"(d) : "r"(bar), "r"(par) : "memory");
    return d;
}
__device__ __forceinline__ void tma_load4(uint32_t dst, const CUtensorMap* m, int c2, int c3, uint32_t bar, uint64_t pol) {
    asm volatile("cp.async.bulk.tensor.4d.shared::cluster.global.mbarrier::complete_tx::bytes.L2::cache_hint [%0], [%1, {%3, %3, %4, %5}], [%2], %6;"
                 :: "r"(dst), "l"(m), "r"(bar), "r"(0), "r"(c2), "r"(c3), "l"(pol) : "memory");
}
__device__ __forceinline__ void ldsm4(uint32_t a, uint32_t& r0, uint32_t& r1, uint32_t& r2, uint32_t& r3) {
    asm volatile("ldmatrix.sync.aligned.m8n8.x4.shared.b16 {%0,%1,%2,%3}, [%4];" : "=r"(r0), "=r"(r1), "=r"(r2), "=r"(r3) : "r"(a) : "memory");
}
__device__ __forceinline__ void ldsm4t(uint32_t a, uint32_t& r0, uint32_t& r1, uint32_t& r2, uint32_t& r3) {
    asm volatile("ldmatrix.sync.aligned.m8n8.x4.trans.shared.b16 {%0,%1,%2,%3}, [%4];" : "=r"(r0), "=r"(r1), "=r"(r2), "=r"(r3) : "r"(a) : "memory");
}
__device__ __forceinline__ void mma16816(float* c, uint32_t a0, uint32_t a1, uint32_t a2, uint32_t a3, uint32_t b0, uint32_t b1) {
    asm volatile("mma.sync.aligned.m16n8k16.row.col.f32.bf16.bf16.f32 {%0,%1,%2,%3}, {%4,%5,%6,%7}, {%8,%9}, {%0,%1,%2,%3};"
                 : "+f"(c[0]), "+f"(c[1]), "+f"(c[2]), "+f"(c[3]) : "r"(a0), "r"(a1), "r"(a2), "r"(a3), "r"(b0), "r"(b1));
}
__device__ __forceinline__ void mma1688z(float* c, uint32_t a0, uint32_t a1, uint32_t b0) {
    asm volatile("mma.sync.aligned.m16n8k8.row.col.f32.bf16.bf16.f32 {%0,%1,%2,%3}, {%4,%5}, {%6}, {%7,%7,%7,%7};"
                 : "=f"(c[0]), "=f"(c[1]), "=f"(c[2]), "=f"(c[3]) : "r"(a0), "r"(a1), "r"(b0), "f"(0.f));
}
__device__ __forceinline__ uint32_t pack2(float lo, float hi) { uint32_t r; asm("cvt.rn.bf16x2.f32 %0, %1, %2;" : "=r"(r) : "f"(hi), "f"(lo)); return r; }
__device__ __forceinline__ float ex2(float x) { float y; asm("ex2.approx.ftz.f32 %0, %1;" : "=f"(y) : "f"(x)); return y; }
__device__ __forceinline__ uint32_t max2(uint32_t a, uint32_t b) { uint32_t r; asm("max.NaN.bf16x2 %0, %1, %2;" : "=r"(r) : "r"(a), "r"(b)); return r; }
__device__ __forceinline__ float bf_lo(uint32_t u) { return __uint_as_float(u << 16); }
__device__ __forceinline__ float bf_hi(uint32_t u) { return __uint_as_float(u & 0xffff0000u); }
__device__ __forceinline__ float rcpa(float x) { float y; asm("rcp.approx.ftz.f32 %0, %1;" : "=f"(y) : "f"(x)); return y; }
__device__ __forceinline__ uint32_t mapa(uint32_t a, int r) { uint32_t o; asm("mapa.shared::cluster.u32 %0, %1, %2;" : "=r"(o) : "r"(a), "r"(r)); return o; }
__device__ __forceinline__ bool elect_one() { uint32_t p; asm volatile("{\n.reg .pred P;\nelect.sync _|P, 0xffffffff;\nselp.u32 %0, 1, 0, P;\n}" : "=r"(p)); return p; }
__device__ __forceinline__ void st_async4(uint32_t a, uint32_t x, uint32_t y, uint32_t z, uint32_t w, uint32_t b) {
    asm volatile("st.async.weak.shared::cluster.mbarrier::complete_tx::bytes.v4.b32 [%0], {%1,%2,%3,%4}, [%5];" :: "r"(a), "r"(x), "r"(y), "r"(z), "r"(w), "r"(b) : "memory");
}
__device__ __forceinline__ float4 lds4(uint32_t a) { float4 x; asm volatile("ld.shared.v4.f32 {%0,%1,%2,%3}, [%4];" : "=f"(x.x), "=f"(x.y), "=f"(x.z), "=f"(x.w) : "r"(a) : "memory"); return x; }
__device__ __forceinline__ float2 lds2(uint32_t a) { float2 x; asm volatile("ld.shared.v2.f32 {%0,%1}, [%2];" : "=f"(x.x), "=f"(x.y) : "r"(a) : "memory"); return x; }
__device__ __forceinline__ uint4 ldsu4(uint32_t a) { uint4 x; asm volatile("ld.shared.v4.u32 {%0,%1,%2,%3}, [%4];" : "=r"(x.x), "=r"(x.y), "=r"(x.z), "=r"(x.w) : "r"(a) : "memory"); return x; }

__device__ __forceinline__ void stg4(void* p, uint4 v) {
    asm volatile("st.global.v4.u32 [%0], {%1,%2,%3,%4};" :: "l"(p), "r"(v.x), "r"(v.y), "r"(v.z), "r"(v.w) : "memory");
}
__device__ __forceinline__ uint4 shfl_xor4(uint4 v, int m) {
    return make_uint4(__shfl_xor_sync(~0u, v.x, m), __shfl_xor_sync(~0u, v.y, m), __shfl_xor_sync(~0u, v.z, m), __shfl_xor_sync(~0u, v.w, m));
}

__global__ void __launch_bounds__(NTHR, 2)
linformer_kernel(const __grid_constant__ Params pp,
                 const __grid_constant__ CUtensorMap mk, const __grid_constant__ CUtensorMap mv,
                 const __grid_constant__ CUtensorMap me, const __grid_constant__ CUtensorMap mf,
                 const __grid_constant__ CUtensorMap mq) {
    const uint64_t pol = 0x12F0000000000000ull;
    const unsigned b = blockIdx.x;
    const int tid = threadIdx.x, lane = tid & 31;
    if (tid == 32)
        asm volatile("cp.async.bulk.prefetch.L2.global.L2::cache_hint [%0], %1, %2;"
                     :: "l"(pp.kv[b & 1] + (((b >> 3) << 18) | ((b & 6) << 14))), "r"(NPRE * UB), "l"(pol) : "memory");
    const int grp = b >> 4, j = b & 15;
    const int isv = j & 1, dh = (j >> 1) & 1, nh = j >> 2;
    const int kvr = (b >> 3) * 128 + (nh & 1) * 8;
    const int qr = (b >> 3) * 128 + (j & 7) * 4;
    extern __shared__ __align__(1024) char smem_raw[];
    const uint32_t sbase = smem_u32(smem_raw);
    const uint32_t sproj = sbase + STAGES * UB, srecv = sproj + 8192, sfrag = srecv + 8192;
    const uint32_t bfull = sfrag + 16384, bempty = bfull + 8 * STAGES, bproj = bempty + 8 * STAGES, bfl = bproj + 8, bfr = bfl + 32;
    const int warp = __shfl_sync(~0u, tid >> 5, 0);
    const CUtensorMap* mkv = isv ? &mv : &mk;
    const bool el = elect_one();
    const int cls = grp == 7;
    if (warp == 0) {
        unsigned tz; asm volatile("mov.u32 %0, %%globaltimer_lo;" : "=r"(tz));
        if (el) {
            #pragma unroll
            for (int p = 0; p < NPRE; p++) mbar_init(bfull + 8 * p, 1);
            mbar_init(bproj, 1);
            mbar_expect_tx(bproj, 8192);
            tma_load4(sproj, isv ? &mf : &me, nh & 1, (nh >> 1) * 8, bproj, 0x1000000000000000ull  );
            #pragma unroll
            for (int p = 0; p < NPRE; p++) {
                mbar_expect_tx(bfull + 8 * p, UB);
                tma_load4(sbase + p * UB, mkv, dh, kvr + p * 16, bfull + 8 * p, pol);
            }
        }
        asm volatile("bar.arrive 2, 128;" ::: "memory");
        if (el) asm volatile("prefetch.tensormap [%0];" :: "l"(&mq) : "memory");
        const Sched& sc = pp.c[cls];
        unsigned long long m = sc.qm >> NPRE;
        unsigned long long sg0 = sc.seg0, sg1 = sc.seg1;
        unsigned dl = tz + sc.off;
        const unsigned slack = sc.slack;
        int ck = kvr + NPRE * 16, cq = qr;
        int s = NPRE, su = NPRE - sc.w + STAGES;
        unsigned ph = 1, phu = 1;
        if (su >= STAGES) { su -= STAGES; phu = 0; }
        asm volatile("bar.sync 1, %0;" :: "n"(NTHR) : "memory");
        asm volatile("barrier.cluster.arrive.relaxed.aligned;" ::: "memory");
        #pragma unroll 1
        for (int t = NPRE; t < NU; t++) {
            const bool isq = m & 1; m >>= 1;
            const CUtensorMap* mp = isq ? &mq : mkv;
            const int c2 = isq ? 0 : dh, c3 = isq ? cq : ck;
            int it = 0;
            unsigned now;
            while (true) {
                const uint32_t slot_free = mbar_test(bempty + 8 * s, ph), landed = mbar_test(bfull + 8 * su, phu);
                asm volatile("mov.u32 %0, %%globaltimer_lo;" : "=r"(now));
                if (slot_free && landed && (int)(now - dl) >= 0) break;
                if (++it > (1 << 22)) __trap();
            }
            if (el) {
                mbar_expect_tx(bfull + 8 * s, UB);
                tma_load4(sbase + s * UB, mp, c2, c3, bfull + 8 * s, pol);
            }
            if (isq) { cq += 32; if ((cq & 0x60) == 0) cq += 2048 - 128; } else { ck += 16; if ((ck & 0x70) == 0) ck += 2048 - 128; }
            if (t == (int)(((unsigned)sg0 >> 10) & 63)) { sg0 = (sg0 >> 16) | (sg1 << 48); sg1 >>= 16; }
            if ((int)(now - slack - dl) > 0) dl = now - slack;
            dl += ((unsigned)sg0 & 1023) * 2;
            if (++s == STAGES) { s = 0; ph ^= 1; }
            if (++su == STAGES) { su = 0; phu ^= 1; }
        }
        asm volatile("barrier.cluster.wait.aligned;" ::: "memory");
        return;
    }
    const unsigned long long qm = pp.c[cls].qm;
    if (warp <= 3) {
        asm volatile("bar.sync 2, 128;" ::: "memory");
        if (el) {
            if (warp == 1) {
                #pragma unroll
                for (int i = 0; i < STAGES; i++) mbar_init(bempty + 8 * i, 4);
            } else if (warp == 2) {
                #pragma unroll
                for (int i = NPRE; i < STAGES; i++) mbar_init(bfull + 8 * i, 1);
                #pragma unroll
                for (int i = 0; i < 4; i++) mbar_init(bfl + 8 * i, 1);
                #pragma unroll
                for (int i = 0; i < 4; i++) mbar_expect_tx(bfl + 8 * i, 2048);
                asm volatile("fence.mbarrier_init.release.cluster;" ::: "memory");
            } else {
                #pragma unroll
                for (int i = 0; i < 4; i++) mbar_init(bfr + 16 * i, 1);
                #pragma unroll
                for (int i = 0; i < 4; i++) mbar_expect_tx(bfr + 16 * i, 4096);
                asm volatile("fence.mbarrier_init.release.cluster;" ::: "memory");
            }
        }
    }
    asm volatile("bar.sync 1, %0;" :: "n"(NTHR) : "memory");
    asm volatile("barrier.cluster.arrive.relaxed.aligned;" ::: "memory");
    const int g = lane >> 2;
    const int mi = lane >> 3, li = lane & 7;
    if (warp == 5) {
        const uint32_t ad0 = isv ? srecv + ((4 * (lane & 1) + ((lane >> 3) & 1)) * 4 + ((lane >> 1) & 3)) * 16 + (lane >> 4) * 8 : srecv + lane * 16;
        uint32_t rbase[8];
        #pragma unroll
        for (int rr = 0; rr < 8; rr++) rbase[rr] = mapa(sbase, (2 * rr + (lane >> 4) + j + 1) & 15) - sbase;
        const uint32_t la0 = sfrag + (isv * 8 + dh * 4 + nh) * 256 + (lane & 15) * 16;
        asm volatile("barrier.cluster.wait.aligned;" ::: "memory");
        #pragma unroll 1
        for (int hg = 0; hg < 4; hg++) {
            const uint32_t ad = ad0 + hg * 2048;
            mbar_wait_cluster(bfl + hg * 8);
            uint32_t o0, o1;
            if (!isv) {
                float4 x = lds4(ad), y = lds4(ad + 512), z = lds4(ad + 1024), v = lds4(ad + 1536);
                uint32_t k0 = pack2((x.x + y.x) + (z.x + v.x), (x.y + y.y) + (z.y + v.y));
                uint32_t k1 = pack2((x.z + y.z) + (z.z + v.z), (x.w + y.w) + (z.w + v.w));
                asm volatile("movmatrix.sync.aligned.m8n8.trans.b16 %0, %1;" : "=r"(o0) : "r"(k0));
                asm volatile("movmatrix.sync.aligned.m8n8.trans.b16 %0, %1;" : "=r"(o1) : "r"(k1));
            } else {
                float2 x = lds2(ad), y = lds2(ad + 512), z = lds2(ad + 1024), v = lds2(ad + 1536);
                float2 x2 = lds2(ad + 128), y2 = lds2(ad + 640), z2 = lds2(ad + 1152), v2 = lds2(ad + 1664);
                o0 = pack2((x.x + y.x) + (z.x + v.x), (x.y + y.y) + (z.y + v.y));
                o1 = pack2((x2.x + y2.x) + (z2.x + v2.x), (x2.y + y2.y) + (z2.y + v2.y));
            }
            const int sl = (lane & 15) * 2;
            const uint32_t w0 = __shfl_sync(~0u, o0, sl), w1 = __shfl_sync(~0u, o1, sl), w2 = __shfl_sync(~0u, o0, sl + 1), w3 = __shfl_sync(~0u, o1, sl + 1);
            const uint32_t la = la0 + hg * 4096, lb = bfr + hg * 16;
            #pragma unroll
            for (int rr = 0; rr < 8; rr++) st_async4(la + rbase[rr], w0, w1, w2, w3, lb + rbase[rr]);
        }
        return;
    }
    const int w = (warp - 1 - (warp > 5)) & 3;
    int n0 = w >> 1, n1 = 14;
    if (warp < 5) {
        const int dr = (j & 3) | (w << 2);
        const uint32_t ra = mapa(srecv + nh * 512 + lane * 16, dr), rb = mapa(bfl, dr);
        const uint32_t aoff = sbase + ((mi >> 1) * 8 + li) * 128 + (((2 * w + (mi & 1)) ^ li) << 4);
        const uint32_t boff = sproj + li * 128 + ((mi ^ li) << 4);
        unsigned long long m = ~qm, gm = qm << STAGES;
        int s = 0; unsigned par = 0;
        asm volatile("barrier.cluster.wait.aligned;" ::: "memory");
        mbar_wait(bproj, 0);
        #pragma unroll 1
        for (int hg = 0; hg < 4; hg++) {
            float acc[2][4] = {};
            #pragma unroll 1
            for (int i = 0; i < 8; i++) {
                uint32_t bb[8];
                ldsm4(boff + i * 1024, bb[0], bb[1], bb[2], bb[3]);
                ldsm4((boff ^ 64) + i * 1024, bb[4], bb[5], bb[6], bb[7]);
                if (gm & 1) mbar_wait(bempty + 8 * s, par ^ 1);
                mbar_wait(bfull + 8 * s, par);
                uint32_t a[4][4];
                #pragma unroll
                for (int ks = 0; ks < 4; ks++) ldsm4t(aoff + s * UB + ks * 2048, a[ks][0], a[ks][1], a[ks][2], a[ks][3]);
                #pragma unroll
                for (int ks = 0; ks < 4; ks++) mma16816(acc[ks & 1], a[ks][0], a[ks][1], a[ks][2], a[ks][3], bb[2 * ks], bb[2 * ks + 1]);
                if (i == 7)
                    st_async4(ra + hg * 2048, __float_as_uint(acc[0][0] + acc[1][0]), __float_as_uint(acc[0][1] + acc[1][1]),
                              __float_as_uint(acc[0][2] + acc[1][2]), __float_as_uint(acc[0][3] + acc[1][3]), rb + hg * 8);
                __syncwarp();
                if (lane == 0) mbar_arrive(bempty + 8 * s);
                const int dt = __ffs((unsigned)(m >> 1));
                m >>= dt; gm >>= dt; s += dt;
                if (s >= STAGES) { s -= STAGES; par ^= 1; }
            }
        }
        n0 += 14; n1 = 16;
    } else {
        asm volatile("barrier.cluster.wait.aligned;" ::: "memory");
    }
    const int rg = w & 1;
    const uint32_t qoff = sbase + (rg * 2 + (mi & 1)) * 2048 + li * 128;
    const uint32_t qx = (mi >> 1) ^ li;
    bf16* obase = pp.out + (size_t)(qr * 8 + rg * 16 + (g & 6)) * DH + (lane & 7) * 8;
    uint32_t kp[16], vp[16];
    unsigned long long m = qm;
    if (warp < 5) m = 3ull << 46;
    if (w & 2) m &= m - 1;
    #pragma unroll 1
    for (int n = n0; n < n1; n += 2) {
        const int t = __ffsll(m) - 1; m &= m - 1; m &= m - 1;
        const int r = (t * 26) >> 8, s = t - r * STAGES;
        const unsigned par = r & 1;
        const int hg = n >> 2;
        bf16* orow = obase + (size_t)(n * 32 + hg * (2048 - 128)) * 8 * DH;
        if (t >= STAGES) mbar_wait(bempty + 8 * s, par ^ 1);
        mbar_wait(bfull + 8 * s, par);
        uint32_t a[8][4];
        #pragma unroll
        for (int ks = 0; ks < 8; ks++) ldsm4(qoff + s * UB + (ks >> 2) * 1024 + ((qx ^ ((ks & 3) << 1)) << 4), a[ks][0], a[ks][1], a[ks][2], a[ks][3]);
        if ((n & 2) == 0 || n == n0) {
            mbar_wait_cluster(bfr + 16 * hg);
            #pragma unroll
            for (int i = 0; i < 8; i++)
                asm volatile("ld.shared.v2.u32 {%0,%1}, [%2];" : "=r"(kp[2 * i]), "=r"(kp[2 * i + 1]) : "r"(sfrag + hg * 4096 + i * 256 + lane * 8) : "memory");
            #pragma unroll
            for (int i = 0; i < 4; i++) { uint4 x = ldsu4(sfrag + hg * 4096 + 2048 + i * 512 + lane * 16); vp[4 * i] = x.x; vp[4 * i + 1] = x.y; vp[4 * i + 2] = x.z; vp[4 * i + 3] = x.w; }
        }
        float sc[4][4] = {};
        #pragma unroll
        for (int ks = 0; ks < 8; ks++) mma16816(sc[ks & 3], a[ks][0], a[ks][1], a[ks][2], a[ks][3], kp[2 * ks], kp[2 * ks + 1]);
        __syncwarp();
        if (lane < 2) mbar_arrive(bempty + 8 * s);
        const float scale = 0.08838834764831845f, l2e = 1.4426950408889634f;
        uint32_t u0 = pack2((sc[0][0] + sc[1][0]) + (sc[2][0] + sc[3][0]), (sc[0][2] + sc[1][2]) + (sc[2][2] + sc[3][2]));
        uint32_t u1 = pack2((sc[0][1] + sc[1][1]) + (sc[2][1] + sc[3][1]), (sc[0][3] + sc[1][3]) + (sc[2][3] + sc[3][3]));
        u0 = pack2(bf_lo(u0) * scale, bf_hi(u0) * scale);
        u1 = pack2(bf_lo(u1) * scale, bf_hi(u1) * scale);
        uint32_t mx = max2(u0, u1);
        {
            const uint32_t a1 = __shfl_xor_sync(~0u, mx, 1), a2 = __shfl_xor_sync(~0u, mx, 2), a3 = __shfl_xor_sync(~0u, mx, 3);
            mx = max2(max2(mx, a1), max2(a2, a3));
        }
        const float e0 = ex2((bf_lo(u0) - bf_lo(mx)) * l2e), e1 = ex2((bf_lo(u1) - bf_lo(mx)) * l2e);
        const float e2 = ex2((bf_hi(u0) - bf_hi(mx)) * l2e), e3 = ex2((bf_hi(u1) - bf_hi(mx)) * l2e);
        float s0 = e0 + e1, s1 = e2 + e3;
        {
            const float a1 = __shfl_xor_sync(~0u, s0, 1), b1 = __shfl_xor_sync(~0u, s1, 1);
            const float a2 = __shfl_xor_sync(~0u, s0, 2), b2 = __shfl_xor_sync(~0u, s1, 2);
            const float a3 = __shfl_xor_sync(~0u, s0, 3), b3 = __shfl_xor_sync(~0u, s1, 3);
            s0 = (s0 + a1) + (a2 + a3); s1 = (s1 + b1) + (b2 + b3);
        }
        const float r0 = rcpa(s0), r1 = rcpa(s1);
        const uint32_t pa0 = pack2(e0 * r0, e1 * r0), pa1 = pack2(e2 * r1, e3 * r1);
        #pragma unroll
        for (int H = 0; H < 2; H++) {
            uint4 lo[2], hi[2];
            #pragma unroll
            for (int J = 0; J < 2; J++) {
                float c[4][4];
                #pragma unroll
                for (int u = 0; u < 4; u++) mma1688z(c[u], pa0, pa1, vp[H * 8 + J * 4 + u]);
                lo[J] = make_uint4(pack2(c[0][0], c[0][1]), pack2(c[1][0], c[1][1]), pack2(c[2][0], c[2][1]), pack2(c[3][0], c[3][1]));
                hi[J] = make_uint4(pack2(c[0][2], c[0][3]), pack2(c[1][2], c[1][3]), pack2(c[2][2], c[2][3]), pack2(c[3][2], c[3][3]));
            }
            const bool od = g & 1;
            const uint4 xl = shfl_xor4(od ? lo[0] : lo[1], 4), xh = shfl_xor4(od ? hi[0] : hi[1], 4);
            bf16* pe = orow + H * 64;
            stg4(pe, od ? xl : lo[0]);
            stg4(pe + DH, od ? lo[1] : xl);
            stg4(pe + 8 * DH, od ? xh : hi[0]);
            stg4(pe + 9 * DH, od ? hi[1] : xh);
        }
    }
}

typedef CUresult (*EncodeFn)(CUtensorMap*, CUtensorMapDataType, cuuint32_t, void*, const cuuint64_t*, const cuuint64_t*,
                             const cuuint32_t*, const cuuint32_t*, CUtensorMapInterleave, CUtensorMapSwizzle,
                             CUtensorMapL2promotion, CUtensorMapFloatOOBfill);

void make_rows_map(EncodeFn enc, CUtensorMap* m, void* p, int halves, int groups) {
    cuuint32_t es[4] = {1, 1, 1, 1};
    cuuint64_t d[4] = {64, 8, 2, 8192};
    cuuint64_t s[3] = {256, 128, 2048};
    cuuint32_t b[4] = {64, 8, (cuuint32_t)halves, (cuuint32_t)groups};
    enc(m, CU_TENSOR_MAP_DATA_TYPE_BFLOAT16, 4, p, d, s, b, es, CU_TENSOR_MAP_INTERLEAVE_NONE, CU_TENSOR_MAP_SWIZZLE_128B,
        CU_TENSOR_MAP_L2_PROMOTION_L2_128B, CU_TENSOR_MAP_FLOAT_OOB_FILL_NONE);
}
void make_proj_map(EncodeFn enc, CUtensorMap* m, void* p) {
    cuuint32_t es[4] = {1, 1, 1, 1};
    cuuint64_t d[4] = {64, 8, 2, 16};
    cuuint64_t s[3] = {4096, 128, 256};
    cuuint32_t b[4] = {64, 8, 1, 8};
    enc(m, CU_TENSOR_MAP_DATA_TYPE_BFLOAT16, 4, p, d, s, b, es, CU_TENSOR_MAP_INTERLEAVE_NONE, CU_TENSOR_MAP_SWIZZLE_128B,
        CU_TENSOR_MAP_L2_PROMOTION_L2_128B, CU_TENSOR_MAP_FLOAT_OOB_FILL_NONE);
}
Sched make_sched(const char* order, int w, int slack, int off, const int (&step)[NSEG]) {
    static const int next[NSEG] = {7, 12, 20, 30, 40, 44, 63};
    Sched s = {};
    for (int t = 0; t < NU; t++) if (order[t] == 'Q') s.qm |= 1ull << t;
    for (int i = 0; i < NSEG; i++) {
        const unsigned long long f = (unsigned long long)(step[i] / 2) | (unsigned long long)next[i] << 10;
        if (i < 4) s.seg0 |= f << (16 * i); else s.seg1 |= f << (16 * (i - 4));
    }
    s.off = off; s.slack = (unsigned short)slack; s.w = (unsigned short)w;
    return s;
}

void launch(void* const* d_in, void* d_out, const Sched& s0, const Sched& s1) {
    void* fn = nullptr;
    cudaDriverEntryPointQueryResult qr;
    cudaGetDriverEntryPoint("cuTensorMapEncodeTiled", &fn, cudaEnableDefault, &qr);
    EncodeFn enc = (EncodeFn)fn;
    CUtensorMap mq, mk, mv, me, mf;
    make_rows_map(enc, &mq, d_in[0], 2, 4);
    make_rows_map(enc, &mk, d_in[1], 1, 8);
    make_rows_map(enc, &mv, d_in[2], 1, 8);
    make_proj_map(enc, &me, d_in[3]);
    make_proj_map(enc, &mf, d_in[4]);
    Params pp;
    pp.kv[0] = (const char*)d_in[1]; pp.kv[1] = (const char*)d_in[2];
    pp.out = (bf16*)d_out;
    pp.c[0] = s0; pp.c[1] = s1;
    cudaFuncSetAttribute(linformer_kernel, cudaFuncAttributeMaxDynamicSharedMemorySize, SMEM_BYTES);
    cudaFuncSetAttribute(linformer_kernel, cudaFuncAttributeNonPortableClusterSizeAllowed, 1);
    cudaLaunchConfig_t cfg = {};
    cfg.gridDim = dim3(128);
    cfg.blockDim = dim3(NTHR);
    cfg.dynamicSmemBytes = SMEM_BYTES;
    cfg.stream = cudaStreamPerThread;
    cudaLaunchAttribute at[2];
    at[0].id = cudaLaunchAttributeClusterDimension;
    at[0].val.clusterDim.x = 16; at[0].val.clusterDim.y = 1; at[0].val.clusterDim.z = 1;
    at[1].id = cudaLaunchAttributeClusterSchedulingPolicyPreference;
    at[1].val.clusterSchedulingPolicyPreference = cudaClusterSchedulingPolicyLoadBalancing;
    cfg.attrs = at; cfg.numAttrs = 2;
    cudaLaunchKernelEx(&cfg, linformer_kernel, pp, mk, mv, me, mf, mq);
}

}

extern "C" void kernel_launch(void* const* d_in, const int* in_sizes, int n_in, void* d_out, int out_size) {
    (void)in_sizes; (void)n_in; (void)out_size;
    const char* order = "KKKKKKKKKQKKQKKQKKQKKQKKQKKQKKQKKQKKQKKQKKKQQQQQ";
    lf::launch(d_in, d_out,
               lf::make_sched(order, 8, 300, 640, {332, 332, 330, 332, 334, 336, 330}),
               lf::make_sched(order, 9, 300, 730, {326, 306, 292, 298, 302, 292, 282}));
}
```

```cpp
#include <cuda_runtime.h>
#include <cuda_bf16.h>
#include <cuda.h>
#include <stdint.h>

namespace lf {

typedef __nv_bfloat16 bf16;

constexpr int DH = 128;
constexpr int NU = 48;
constexpr int UB = 8192;
constexpr int STAGES = 10;
constexpr int NTHR = 320;
constexpr int NPRE = 4;
constexpr int SMEM_BYTES = STAGES * UB + 8192 + 8192 + 16384 + 1024;


constexpr unsigned long long q_mask(const char* order) {
    unsigned long long m = 0;
    for (int t = 0; t < NU; t++) if (order[t] == 'Q') m |= 1ull << t;
    return m;
}
constexpr unsigned long long QMASK = q_mask("KKKKKKKKKQKKQKKQKKQKKQKKQKKQKKQKKQKQKKQKKKKQQQQQ");

struct Pace { int off, step, up, dn, lag, slack; };
struct Params {
    const char* kv[2];
    bf16* out;
    Pace c[2];
};

__device__ __forceinline__ uint32_t smem_u32(const void* p) { return (uint32_t)__cvta_generic_to_shared(p); }
__device__ __forceinline__ void mbar_init(uint32_t bar, uint32_t cnt) { asm volatile("mbarrier.init.shared::cta.b64 [%0], %1;" :: "r"(bar), "r"(cnt) : "memory"); }
__device__ __forceinline__ void mbar_expect_tx(uint32_t bar, uint32_t bytes) { asm volatile("mbarrier.arrive.expect_tx.shared::cta.b64 _, [%0], %1;" :: "r"(bar), "r"(bytes) : "memory"); }
__device__ __forceinline__ void mbar_arrive(uint32_t bar) { asm volatile("mbarrier.arrive.shared::cta.b64 _, [%0];" :: "r"(bar) : "memory"); }
__device__ __forceinline__ void mbar_wait(uint32_t bar, uint32_t parity) {
    uint32_t done; int it = 0;
    do {
        asm volatile("{\n.reg .pred p;\nmbarrier.try_wait.parity.shared::cta.b64 p, [%1], %2;\nselp.u32 %0, 1, 0, p;\n}" : "=r"(done) : "r"(bar), "r"(parity) : "memory");
        if (++it > (1 << 22)) __trap();
    } while (!done);
}
__device__ __forceinline__ void mbar_wait_cluster(uint32_t bar) {
    uint32_t done; int it = 0;
    do {
        asm volatile("{\n.reg .pred p;\nmbarrier.try_wait.parity.acquire.cluster.shared::cta.b64 p, [%1], 0;\nselp.u32 %0, 1, 0, p;\n}" : "=r"(done) : "r"(bar) : "memory");
        if (++it > (1 << 22)) __trap();
    } while (!done);
}
__device__ __forceinline__ uint32_t mbar_test(uint32_t bar, uint32_t par) {
    uint32_t d;
    asm volatile("{\n.reg .pred p;\nmbarrier.test_wait.parity.shared::cta.b64 p, [%1], %2;\nselp.u32 %0, 1, 0, p;\n}" : "=r"(d) : "r"(bar), "r"(par) : "memory");
    return d;
}
__device__ __forceinline__ void tma_load4(uint32_t dst, const CUtensorMap* m, int c2, int c3, uint32_t bar, uint64_t pol) {
    asm volatile("cp.async.bulk.tensor.4d.shared::cluster.global.mbarrier::complete_tx::bytes.L2::cache_hint [%0], [%1, {%3, %3, %4, %5}], [%2], %6;"
                 :: "r"(dst), "l"(m), "r"(bar), "r"(0), "r"(c2), "r"(c3), "l"(pol) : "memory");
}
__device__ __forceinline__ void ldsm4(uint32_t a, uint32_t& r0, uint32_t& r1, uint32_t& r2, uint32_t& r3) {
    asm volatile("ldmatrix.sync.aligned.m8n8.x4.shared.b16 {%0,%1,%2,%3}, [%4];" : "=r"(r0), "=r"(r1), "=r"(r2), "=r"(r3) : "r"(a) : "memory");
}
__device__ __forceinline__ void ldsm4t(uint32_t a, uint32_t& r0, uint32_t& r1, uint32_t& r2, uint32_t& r3) {
    asm volatile("ldmatrix.sync.aligned.m8n8.x4.trans.shared.b16 {%0,%1,%2,%3}, [%4];" : "=r"(r0), "=r"(r1), "=r"(r2), "=r"(r3) : "r"(a) : "memory");
}
__device__ __forceinline__ void mma16816(float* c, uint32_t a0, uint32_t a1, uint32_t a2, uint32_t a3, uint32_t b0, uint32_t b1) {
    asm volatile("mma.sync.aligned.m16n8k16.row.col.f32.bf16.bf16.f32 {%0,%1,%2,%3}, {%4,%5,%6,%7}, {%8,%9}, {%0,%1,%2,%3};"
                 : "+f"(c[0]), "+f"(c[1]), "+f"(c[2]), "+f"(c[3]) : "r"(a0), "r"(a1), "r"(a2), "r"(a3), "r"(b0), "r"(b1));
}
__device__ __forceinline__ void mma1688z(float* c, uint32_t a0, uint32_t a1, uint32_t b0) {
    asm volatile("mma.sync.aligned.m16n8k8.row.col.f32.bf16.bf16.f32 {%0,%1,%2,%3}, {%4,%5}, {%6}, {%7,%7,%7,%7};"
                 : "=f"(c[0]), "=f"(c[1]), "=f"(c[2]), "=f"(c[3]) : "r"(a0), "r"(a1), "r"(b0), "f"(0.f));
}
__device__ __forceinline__ uint32_t pack2(float lo, float hi) { uint32_t r; asm("cvt.rn.bf16x2.f32 %0, %1, %2;" : "=r"(r) : "f"(hi), "f"(lo)); return r; }
__device__ __forceinline__ float ex2(float x) { float y; asm("ex2.approx.ftz.f32 %0, %1;" : "=f"(y) : "f"(x)); return y; }
__device__ __forceinline__ uint32_t max2(uint32_t a, uint32_t b) { uint32_t r; asm("max.NaN.bf16x2 %0, %1, %2;" : "=r"(r) : "r"(a), "r"(b)); return r; }
__device__ __forceinline__ float bf_lo(uint32_t u) { return __uint_as_float(u << 16); }
__device__ __forceinline__ float bf_hi(uint32_t u) { return __uint_as_float(u & 0xffff0000u); }
__device__ __forceinline__ float rcpa(float x) { float y; asm("rcp.approx.ftz.f32 %0, %1;" : "=f"(y) : "f"(x)); return y; }
__device__ __forceinline__ uint32_t mapa(uint32_t a, int r) { uint32_t o; asm("mapa.shared::cluster.u32 %0, %1, %2;" : "=r"(o) : "r"(a), "r"(r)); return o; }
__device__ __forceinline__ bool elect_one() { uint32_t p; asm volatile("{\n.reg .pred P;\nelect.sync _|P, 0xffffffff;\nselp.u32 %0, 1, 0, P;\n}" : "=r"(p)); return p; }
__device__ __forceinline__ void st_async4(uint32_t a, uint32_t x, uint32_t y, uint32_t z, uint32_t w, uint32_t b) {
    asm volatile("st.async.weak.shared::cluster.mbarrier::complete_tx::bytes.v4.b32 [%0], {%1,%2,%3,%4}, [%5];" :: "r"(a), "r"(x), "r"(y), "r"(z), "r"(w), "r"(b) : "memory");
}
__device__ __forceinline__ float4 lds4(uint32_t a) { float4 x; asm volatile("ld.shared.v4.f32 {%0,%1,%2,%3}, [%4];" : "=f"(x.x), "=f"(x.y), "=f"(x.z), "=f"(x.w) : "r"(a) : "memory"); return x; }
__device__ __forceinline__ float2 lds2(uint32_t a) { float2 x; asm volatile("ld.shared.v2.f32 {%0,%1}, [%2];" : "=f"(x.x), "=f"(x.y) : "r"(a) : "memory"); return x; }
__device__ __forceinline__ uint4 ldsu4(uint32_t a) { uint4 x; asm volatile("ld.shared.v4.u32 {%0,%1,%2,%3}, [%4];" : "=r"(x.x), "=r"(x.y), "=r"(x.z), "=r"(x.w) : "r"(a) : "memory"); return x; }

__device__ __forceinline__ void stg4(void* p, uint4 v) {
    asm volatile("st.global.v4.u32 [%0], {%1,%2,%3,%4};" :: "l"(p), "r"(v.x), "r"(v.y), "r"(v.z), "r"(v.w) : "memory");
}
__device__ __forceinline__ uint4 shfl_xor4(uint4 v, int m) {
    return make_uint4(__shfl_xor_sync(~0u, v.x, m), __shfl_xor_sync(~0u, v.y, m), __shfl_xor_sync(~0u, v.z, m), __shfl_xor_sync(~0u, v.w, m));
}

__global__ void __launch_bounds__(NTHR, 2)
linformer_kernel(const __grid_constant__ Params pp,
                 const __grid_constant__ CUtensorMap mk, const __grid_constant__ CUtensorMap mv,
                 const __grid_constant__ CUtensorMap me, const __grid_constant__ CUtensorMap mf,
                 const __grid_constant__ CUtensorMap mq) {
    const uint64_t pol = 0x12F0000000000000ull;
    const unsigned b = blockIdx.x;
    const int tid = threadIdx.x, lane = tid & 31;
    if (tid == 32)
        asm volatile("cp.async.bulk.prefetch.L2.global.L2::cache_hint [%0], %1, %2;"
                     :: "l"(pp.kv[b & 1] + (((b >> 3) << 18) | ((b & 6) << 14))), "r"(NPRE * UB), "l"(pol) : "memory");
    const int grp = b >> 4, j = b & 15;
    const int isv = j & 1, dh = (j >> 1) & 1, nh = j >> 2;
    const int kvr = (b >> 3) * 128 + (nh & 1) * 8;
    const int qr = (b >> 3) * 128 + (j & 7) * 4;
    extern __shared__ __align__(1024) char smem_raw[];
    const uint32_t sbase = smem_u32(smem_raw);
    const uint32_t sproj = sbase + STAGES * UB, srecv = sproj + 8192, sfrag = srecv + 8192;
    const uint32_t bfull = sfrag + 16384, bempty = bfull + 8 * STAGES, bproj = bempty + 8 * STAGES, bfl = bproj + 8, bfr = bfl + 32;
    const int warp = __shfl_sync(~0u, tid >> 5, 0);
    const CUtensorMap* mkv = isv ? &mv : &mk;
    const bool el = elect_one();
    if (warp == 0) {
        unsigned tz; asm volatile("mov.u32 %0, %%globaltimer_lo;" : "=r"(tz));
        if (el) {
            #pragma unroll
            for (int p = 0; p < NPRE; p++) mbar_init(bfull + 8 * p, 1);
            mbar_init(bproj, 1);
            mbar_expect_tx(bproj, 8192);
            tma_load4(sproj, isv ? &mf : &me, nh & 1, (nh >> 1) * 8, bproj, 0x1000000000000000ull  );
            #pragma unroll
            for (int p = 0; p < NPRE; p++) {
                mbar_expect_tx(bfull + 8 * p, UB);
                tma_load4(sbase + p * UB, mkv, dh, kvr + p * 16, bfull + 8 * p, pol);
            }
        }
        asm volatile("bar.arrive 2, 128;" ::: "memory");
        if (el) asm volatile("prefetch.tensormap [%0];" :: "l"(&mq) : "memory");
        const Pace& pc = pp.c[grp == 7];
        const int step = pc.step, slow = step + pc.up, fast = step - pc.dn, slack = pc.slack;
        unsigned long long m = QMASK >> NPRE;
        unsigned dl = tz + pc.off;
        int ck = kvr + NPRE * 16, cq = qr;
        int s = NPRE, sv = NPRE - pc.lag;
        unsigned ph = 1, phv = 0;
        asm volatile("bar.sync 1, %0;" :: "n"(NTHR) : "memory");
        asm volatile("barrier.cluster.arrive.relaxed.aligned;" ::: "memory");
        #pragma unroll 1
        for (int t = NPRE; t < NU; t++) {
            const bool isq = m & 1; m >>= 1;
            const CUtensorMap* mp = isq ? &mq : mkv;
            const int c2 = isq ? 0 : dh, c3 = isq ? cq : ck;
            int it = 0;
            unsigned now;
            while (true) {
                const uint32_t slot_free = mbar_test(bempty + 8 * s, ph);
                asm volatile("mov.u32 %0, %%globaltimer_lo;" : "=r"(now));
                if (slot_free && (int)(now - dl) >= 0) break;
                if (++it > (1 << 22)) __trap();
            }
            if (el) {
                mbar_expect_tx(bfull + 8 * s, UB);
                tma_load4(sbase + s * UB, mp, c2, c3, bfull + 8 * s, pol);
            }
            if (isq) { cq += 32; if ((cq & 0x60) == 0) cq += 2048 - 128; } else { ck += 16; if ((ck & 0x70) == 0) ck += 2048 - 128; }
            if ((int)(now - slack - dl) > 0) dl = now - slack;
            dl += t < 8 ? step : mbar_test(bfull + 8 * sv, phv) ? fast : slow;
            if (++s == STAGES) { s = 0; ph ^= 1; }
            if (++sv == STAGES) { sv = 0; phv ^= 1; }
        }
        asm volatile("barrier.cluster.wait.aligned;" ::: "memory");
        return;
    }
    if (warp <= 3) {
        asm volatile("bar.sync 2, 128;" ::: "memory");
        if (el) {
            if (warp == 1) {
                #pragma unroll
                for (int i = 0; i < STAGES; i++) mbar_init(bempty + 8 * i, 4);
            } else if (warp == 2) {
                #pragma unroll
                for (int i = NPRE; i < STAGES; i++) mbar_init(bfull + 8 * i, 1);
                #pragma unroll
                for (int i = 0; i < 4; i++) mbar_init(bfl + 8 * i, 1);
                #pragma unroll
                for (int i = 0; i < 4; i++) mbar_expect_tx(bfl + 8 * i, 2048);
                asm volatile("fence.mbarrier_init.release.cluster;" ::: "memory");
            } else {
                #pragma unroll
                for (int i = 0; i < 4; i++) mbar_init(bfr + 16 * i, 1);
                #pragma unroll
                for (int i = 0; i < 4; i++) mbar_expect_tx(bfr + 16 * i, 4096);
                asm volatile("fence.mbarrier_init.release.cluster;" ::: "memory");
            }
        }
    }
    asm volatile("bar.sync 1, %0;" :: "n"(NTHR) : "memory");
    asm volatile("barrier.cluster.arrive.relaxed.aligned;" ::: "memory");
    const int g = lane >> 2;
    const int mi = lane >> 3, li = lane & 7;
    if (warp == 5) {
        const uint32_t ad0 = isv ? srecv + ((4 * (lane & 1) + ((lane >> 3) & 1)) * 4 + ((lane >> 1) & 3)) * 16 + (lane >> 4) * 8 : srecv + lane * 16;
        uint32_t rbase[8];
        #pragma unroll
        for (int rr = 0; rr < 8; rr++) rbase[rr] = mapa(sbase, (2 * rr + (lane >> 4) + j + 1) & 15) - sbase;
        const uint32_t la0 = sfrag + (isv * 8 + dh * 4 + nh) * 256 + (lane & 15) * 16;
        asm volatile("barrier.cluster.wait.aligned;" ::: "memory");
        #pragma unroll 1
        for (int hg = 0; hg < 4; hg++) {
            const uint32_t ad = ad0 + hg * 2048;
            mbar_wait_cluster(bfl + hg * 8);
            uint32_t o0, o1;
            if (!isv) {
                float4 x = lds4(ad), y = lds4(ad + 512), z = lds4(ad + 1024), v = lds4(ad + 1536);
                uint32_t k0 = pack2((x.x + y.x) + (z.x + v.x), (x.y + y.y) + (z.y + v.y));
                uint32_t k1 = pack2((x.z + y.z) + (z.z + v.z), (x.w + y.w) + (z.w + v.w));
                asm volatile("movmatrix.sync.aligned.m8n8.trans.b16 %0, %1;" : "=r"(o0) : "r"(k0));
                asm volatile("movmatrix.sync.aligned.m8n8.trans.b16 %0, %1;" : "=r"(o1) : "r"(k1));
            } else {
                float2 x = lds2(ad), y = lds2(ad + 512), z = lds2(ad + 1024), v = lds2(ad + 1536);
                float2 x2 = lds2(ad + 128), y2 = lds2(ad + 640), z2 = lds2(ad + 1152), v2 = lds2(ad + 1664);
                o0 = pack2((x.x + y.x) + (z.x + v.x), (x.y + y.y) + (z.y + v.y));
                o1 = pack2((x2.x + y2.x) + (z2.x + v2.x), (x2.y + y2.y) + (z2.y + v2.y));
            }
            const int sl = (lane & 15) * 2;
            const uint32_t w0 = __shfl_sync(~0u, o0, sl), w1 = __shfl_sync(~0u, o1, sl), w2 = __shfl_sync(~0u, o0, sl + 1), w3 = __shfl_sync(~0u, o1, sl + 1);
            const uint32_t la = la0 + hg * 4096, lb = bfr + hg * 16;
            #pragma unroll
            for (int rr = 0; rr < 8; rr++) st_async4(la + rbase[rr], w0, w1, w2, w3, lb + rbase[rr]);
        }
        return;
    }
    const int w = (warp - 1 - (warp > 5)) & 3;
    int n0 = w >> 1, n1 = 14;
    if (warp < 5) {
        const int dr = (j & 3) | (w << 2);
        const uint32_t ra = mapa(srecv + nh * 512 + lane * 16, dr), rb = mapa(bfl, dr);
        const uint32_t aoff = sbase + ((mi >> 1) * 8 + li) * 128 + (((2 * w + (mi & 1)) ^ li) << 4);
        const uint32_t boff = sproj + li * 128 + ((mi ^ li) << 4);
        unsigned long long m = ~QMASK, gm = QMASK << STAGES;
        int s = 0; unsigned par = 0;
        asm volatile("barrier.cluster.wait.aligned;" ::: "memory");
        mbar_wait(bproj, 0);
        #pragma unroll 1
        for (int hg = 0; hg < 4; hg++) {
            float acc[2][4] = {};
            #pragma unroll 1
            for (int i = 0; i < 8; i++) {
                uint32_t bb[8];
                ldsm4(boff + i * 1024, bb[0], bb[1], bb[2], bb[3]);
                ldsm4((boff ^ 64) + i * 1024, bb[4], bb[5], bb[6], bb[7]);
                if (gm & 1) mbar_wait(bempty + 8 * s, par ^ 1);
                mbar_wait(bfull + 8 * s, par);
                uint32_t a[4][4];
                #pragma unroll
                for (int ks = 0; ks < 4; ks++) ldsm4t(aoff + s * UB + ks * 2048, a[ks][0], a[ks][1], a[ks][2], a[ks][3]);
                #pragma unroll
                for (int ks = 0; ks < 4; ks++) mma16816(acc[ks & 1], a[ks][0], a[ks][1], a[ks][2], a[ks][3], bb[2 * ks], bb[2 * ks + 1]);
                if (i == 7)
                    st_async4(ra + hg * 2048, __float_as_uint(acc[0][0] + acc[1][0]), __float_as_uint(acc[0][1] + acc[1][1]),
                              __float_as_uint(acc[0][2] + acc[1][2]), __float_as_uint(acc[0][3] + acc[1][3]), rb + hg * 8);
                __syncwarp();
                if (lane == 0) mbar_arrive(bempty + 8 * s);
                const int dt = __ffs((unsigned)(m >> 1));
                m >>= dt; gm >>= dt; s += dt;
                if (s >= STAGES) { s -= STAGES; par ^= 1; }
            }
        }
        n0 += 14; n1 = 16;
    } else {
        asm volatile("barrier.cluster.wait.aligned;" ::: "memory");
    }
    const int rg = w & 1;
    const uint32_t qoff = sbase + (rg * 2 + (mi & 1)) * 2048 + li * 128;
    const uint32_t qx = (mi >> 1) ^ li;
    bf16* obase = pp.out + (size_t)(qr * 8 + rg * 16 + (g & 6)) * DH + (lane & 7) * 8;
    uint32_t kp[16], vp[16];
    unsigned long long m = warp < 5 ? 3ull << (NU - 2) : QMASK;
    if (w & 2) m &= m - 1;
    #pragma unroll 1
    for (int n = n0; n < n1; n += 2) {
        const int t = __ffsll(m) - 1; m &= m - 1; m &= m - 1;
        const int r = (t * 26) >> 8, s = t - r * STAGES;
        const unsigned par = r & 1;
        const int hg = n >> 2;
        bf16* orow = obase + (size_t)(n * 32 + hg * (2048 - 128)) * 8 * DH;
        if (t >= STAGES) mbar_wait(bempty + 8 * s, par ^ 1);
        mbar_wait(bfull + 8 * s, par);
        uint32_t a[8][4];
        #pragma unroll
        for (int ks = 0; ks < 8; ks++) ldsm4(qoff + s * UB + (ks >> 2) * 1024 + ((qx ^ ((ks & 3) << 1)) << 4), a[ks][0], a[ks][1], a[ks][2], a[ks][3]);
        if ((n & 2) == 0 || n == n0) {
            mbar_wait_cluster(bfr + 16 * hg);
            #pragma unroll
            for (int i = 0; i < 8; i++)
                asm volatile("ld.shared.v2.u32 {%0,%1}, [%2];" : "=r"(kp[2 * i]), "=r"(kp[2 * i + 1]) : "r"(sfrag + hg * 4096 + i * 256 + lane * 8) : "memory");
            #pragma unroll
            for (int i = 0; i < 4; i++) { uint4 x = ldsu4(sfrag + hg * 4096 + 2048 + i * 512 + lane * 16); vp[4 * i] = x.x; vp[4 * i + 1] = x.y; vp[4 * i + 2] = x.z; vp[4 * i + 3] = x.w; }
        }
        float sc[4][4] = {};
        #pragma unroll
        for (int ks = 0; ks < 8; ks++) mma16816(sc[ks & 3], a[ks][0], a[ks][1], a[ks][2], a[ks][3], kp[2 * ks], kp[2 * ks + 1]);
        __syncwarp();
        if (lane < 2) mbar_arrive(bempty + 8 * s);
        const float scale = 0.08838834764831845f, l2e = 1.4426950408889634f;
        uint32_t u0 = pack2((sc[0][0] + sc[1][0]) + (sc[2][0] + sc[3][0]), (sc[0][2] + sc[1][2]) + (sc[2][2] + sc[3][2]));
        uint32_t u1 = pack2((sc[0][1] + sc[1][1]) + (sc[2][1] + sc[3][1]), (sc[0][3] + sc[1][3]) + (sc[2][3] + sc[3][3]));
        u0 = pack2(bf_lo(u0) * scale, bf_hi(u0) * scale);
        u1 = pack2(bf_lo(u1) * scale, bf_hi(u1) * scale);
        uint32_t mx = max2(u0, u1);
        {
            const uint32_t a1 = __shfl_xor_sync(~0u, mx, 1), a2 = __shfl_xor_sync(~0u, mx, 2), a3 = __shfl_xor_sync(~0u, mx, 3);
            mx = max2(max2(mx, a1), max2(a2, a3));
        }
        const float e0 = ex2((bf_lo(u0) - bf_lo(mx)) * l2e), e1 = ex2((bf_lo(u1) - bf_lo(mx)) * l2e);
        const float e2 = ex2((bf_hi(u0) - bf_hi(mx)) * l2e), e3 = ex2((bf_hi(u1) - bf_hi(mx)) * l2e);
        float s0 = e0 + e1, s1 = e2 + e3;
        {
            const float a1 = __shfl_xor_sync(~0u, s0, 1), b1 = __shfl_xor_sync(~0u, s1, 1);
            const float a2 = __shfl_xor_sync(~0u, s0, 2), b2 = __shfl_xor_sync(~0u, s1, 2);
            const float a3 = __shfl_xor_sync(~0u, s0, 3), b3 = __shfl_xor_sync(~0u, s1, 3);
            s0 = (s0 + a1) + (a2 + a3); s1 = (s1 + b1) + (b2 + b3);
        }
        const float r0 = rcpa(s0), r1 = rcpa(s1);
        const uint32_t pa0 = pack2(e0 * r0, e1 * r0), pa1 = pack2(e2 * r1, e3 * r1);
        #pragma unroll
        for (int H = 0; H < 2; H++) {
            uint4 lo[2], hi[2];
            #pragma unroll
            for (int J = 0; J < 2; J++) {
                float c[4][4];
                #pragma unroll
                for (int u = 0; u < 4; u++) mma1688z(c[u], pa0, pa1, vp[H * 8 + J * 4 + u]);
                lo[J] = make_uint4(pack2(c[0][0], c[0][1]), pack2(c[1][0], c[1][1]), pack2(c[2][0], c[2][1]), pack2(c[3][0], c[3][1]));
                hi[J] = make_uint4(pack2(c[0][2], c[0][3]), pack2(c[1][2], c[1][3]), pack2(c[2][2], c[2][3]), pack2(c[3][2], c[3][3]));
            }
            const bool od = g & 1;
            const uint4 xl = shfl_xor4(od ? lo[0] : lo[1], 4), xh = shfl_xor4(od ? hi[0] : hi[1], 4);
            bf16* pe = orow + H * 64;
            stg4(pe, od ? xl : lo[0]);
            stg4(pe + DH, od ? lo[1] : xl);
            stg4(pe + 8 * DH, od ? xh : hi[0]);
            stg4(pe + 9 * DH, od ? hi[1] : xh);
        }
    }
}

typedef CUresult (*EncodeFn)(CUtensorMap*, CUtensorMapDataType, cuuint32_t, void*, const cuuint64_t*, const cuuint64_t*,
                             const cuuint32_t*, const cuuint32_t*, CUtensorMapInterleave, CUtensorMapSwizzle,
                             CUtensorMapL2promotion, CUtensorMapFloatOOBfill);

void make_rows_map(EncodeFn enc, CUtensorMap* m, void* p, int halves, int groups) {
    cuuint32_t es[4] = {1, 1, 1, 1};
    cuuint64_t d[4] = {64, 8, 2, 8192};
    cuuint64_t s[3] = {256, 128, 2048};
    cuuint32_t b[4] = {64, 8, (cuuint32_t)halves, (cuuint32_t)groups};
    enc(m, CU_TENSOR_MAP_DATA_TYPE_BFLOAT16, 4, p, d, s, b, es, CU_TENSOR_MAP_INTERLEAVE_NONE, CU_TENSOR_MAP_SWIZZLE_128B,
        CU_TENSOR_MAP_L2_PROMOTION_L2_128B, CU_TENSOR_MAP_FLOAT_OOB_FILL_NONE);
}
void make_proj_map(EncodeFn enc, CUtensorMap* m, void* p) {
    cuuint32_t es[4] = {1, 1, 1, 1};
    cuuint64_t d[4] = {64, 8, 2, 16};
    cuuint64_t s[3] = {4096, 128, 256};
    cuuint32_t b[4] = {64, 8, 1, 8};
    enc(m, CU_TENSOR_MAP_DATA_TYPE_BFLOAT16, 4, p, d, s, b, es, CU_TENSOR_MAP_INTERLEAVE_NONE, CU_TENSOR_MAP_SWIZZLE_128B,
        CU_TENSOR_MAP_L2_PROMOTION_L2_128B, CU_TENSOR_MAP_FLOAT_OOB_FILL_NONE);
}

void launch(void* const* d_in, void* d_out, const Pace& s0, const Pace& s1) {
    void* fn = nullptr;
    cudaDriverEntryPointQueryResult qr;
    cudaGetDriverEntryPoint("cuTensorMapEncodeTiled", &fn, cudaEnableDefault, &qr);
    EncodeFn enc = (EncodeFn)fn;
    CUtensorMap mq, mk, mv, me, mf;
    make_rows_map(enc, &mq, d_in[0], 2, 4);
    make_rows_map(enc, &mk, d_in[1], 1, 8);
    make_rows_map(enc, &mv, d_in[2], 1, 8);
    make_proj_map(enc, &me, d_in[3]);
    make_proj_map(enc, &mf, d_in[4]);
    Params pp;
    pp.kv[0] = (const char*)d_in[1]; pp.kv[1] = (const char*)d_in[2];
    pp.out = (bf16*)d_out;
    pp.c[0] = s0; pp.c[1] = s1;
    cudaFuncSetAttribute(linformer_kernel, cudaFuncAttributeMaxDynamicSharedMemorySize, SMEM_BYTES);
    cudaFuncSetAttribute(linformer_kernel, cudaFuncAttributeNonPortableClusterSizeAllowed, 1);
    cudaLaunchConfig_t cfg = {};
    cfg.gridDim = dim3(128);
    cfg.blockDim = dim3(NTHR);
    cfg.dynamicSmemBytes = SMEM_BYTES;
    cfg.stream = cudaStreamPerThread;
    cudaLaunchAttribute at[2];
    at[0].id = cudaLaunchAttributeClusterDimension;
    at[0].val.clusterDim.x = 16; at[0].val.clusterDim.y = 1; at[0].val.clusterDim.z = 1;
    at[1].id = cudaLaunchAttributeClusterSchedulingPolicyPreference;
    at[1].val.clusterSchedulingPolicyPreference = cudaClusterSchedulingPolicyLoadBalancing;
    cfg.attrs = at; cfg.numAttrs = 2;
    cudaLaunchKernelEx(&cfg, linformer_kernel, pp, mk, mv, me, mf, mq);
}

}

extern "C" void kernel_launch(void* const* d_in, const int* in_sizes, int n_in, void* d_out, int out_size) {
    (void)in_sizes; (void)n_in; (void)out_size;
    lf::launch(d_in, d_out, {660, 330, 16, 10, 4, 300}, {820, 294, 16, 10, 5, 300});
}
```

```cpp
#include <cuda_runtime.h>
#include <cuda_bf16.h>
#include <cuda.h>
#include <stdint.h>

namespace lf {

typedef __nv_bfloat16 bf16;

constexpr int DH = 128;
constexpr int NU = 48;
constexpr int UB = 8192;
constexpr int STAGES = 10;
constexpr int NTHR = 320;
constexpr int NPRE = 4;
constexpr int SMEM_BYTES = STAGES * UB + 8192 + 8192 + 16384 + 1024;

constexpr char ORDER[NU + 1] = "KKKKKKKKQKKQKKQKKQKKQKKQKKQKKQKKQKKQKQKQKKKKQQQQ";
constexpr int LAST_KV = 43;
constexpr int unit_pos(char kind, int idx) {
    for (int t = 0; t < NU; t++) if (ORDER[t] == kind && idx-- == 0) return t;
    return -1;
}
constexpr unsigned long long q_mask() {
    unsigned long long m = 0;
    for (int t = 0; t < NU; t++) if (ORDER[t] == 'Q') m |= 1ull << t;
    return m;
}
constexpr bool order_ok() {
    if (unit_pos('K', 31) != LAST_KV || unit_pos('Q', 14) != NU - 2 || unit_pos('Q', 15) != NU - 1 || unit_pos('K', NPRE) != NPRE) return false;
    for (int i = 0; i < 16; i++) {
        if (unit_pos('Q', i) < unit_pos('K', i / 4 * 8 + 7)) return false;
        if (unit_pos('Q', i) - (i < 2 ? unit_pos('K', 3) : i < 14 ? unit_pos('Q', i - 2) : LAST_KV) > STAGES) return false;
    }
    for (int i = 1; i < 32; i++) if (unit_pos('K', i) - unit_pos('K', i - 1) > STAGES) return false;
    for (int h = 0; h < 2; h++)
        if (unit_pos('Q', 4 * h) + STAGES > unit_pos('K', 8 * h + 19) || unit_pos('Q', 4 * h + 2) + STAGES > unit_pos('K', 8 * h + 23)) return false;
    return true;
}
static_assert(order_ok(), "invalid unit order");
constexpr unsigned long long QMASK = q_mask();

struct Pace { int off, step, up, dn, lag, slack, tail0, tail1; };
struct Params {
    const char* k;
    bf16* out;
    Pace c[2];
};

__device__ __forceinline__ uint32_t smem_u32(const void* p) { return (uint32_t)__cvta_generic_to_shared(p); }
__device__ __forceinline__ void mbar_init(uint32_t bar, uint32_t cnt) { asm volatile("mbarrier.init.shared::cta.b64 [%0], %1;" :: "r"(bar), "r"(cnt) : "memory"); }
__device__ __forceinline__ void mbar_expect_tx(uint32_t bar, uint32_t bytes) { asm volatile("mbarrier.arrive.expect_tx.shared::cta.b64 _, [%0], %1;" :: "r"(bar), "r"(bytes) : "memory"); }
__device__ __forceinline__ void mbar_arrive(uint32_t bar) { asm volatile("mbarrier.arrive.shared::cta.b64 _, [%0];" :: "r"(bar) : "memory"); }
__device__ __forceinline__ void mbar_wait(uint32_t bar, uint32_t parity) {
    uint32_t done; int it = 0;
    do {
        asm volatile("{\n.reg .pred p;\nmbarrier.try_wait.parity.shared::cta.b64 p, [%1], %2;\nselp.u32 %0, 1, 0, p;\n}" : "=r"(done) : "r"(bar), "r"(parity) : "memory");
        if (++it > (1 << 22)) __trap();
    } while (!done);
}
__device__ __forceinline__ void mbar_wait_cluster(uint32_t bar) {
    uint32_t done; int it = 0;
    do {
        asm volatile("{\n.reg .pred p;\nmbarrier.try_wait.parity.acquire.cluster.shared::cta.b64 p, [%1], 0;\nselp.u32 %0, 1, 0, p;\n}" : "=r"(done) : "r"(bar) : "memory");
        if (++it > (1 << 22)) __trap();
    } while (!done);
}
__device__ __forceinline__ uint32_t mbar_test(uint32_t bar, uint32_t par) {
    uint32_t d;
    asm volatile("{\n.reg .pred p;\nmbarrier.test_wait.parity.shared::cta.b64 p, [%1], %2;\nselp.u32 %0, 1, 0, p;\n}" : "=r"(d) : "r"(bar), "r"(par) : "memory");
    return d;
}
__device__ __forceinline__ void tma_load4(uint32_t dst, const CUtensorMap* m, int c2, int c3, uint32_t bar, uint64_t pol) {
    asm volatile("cp.async.bulk.tensor.4d.shared::cluster.global.mbarrier::complete_tx::bytes.L2::cache_hint [%0], [%1, {%3, %3, %4, %5}], [%2], %6;"
                 :: "r"(dst), "l"(m), "r"(bar), "r"(0), "r"(c2), "r"(c3), "l"(pol) : "memory");
}
__device__ __forceinline__ void ldsm4(uint32_t a, uint32_t& r0, uint32_t& r1, uint32_t& r2, uint32_t& r3) {
    asm volatile("ldmatrix.sync.aligned.m8n8.x4.shared.b16 {%0,%1,%2,%3}, [%4];" : "=r"(r0), "=r"(r1), "=r"(r2), "=r"(r3) : "r"(a) : "memory");
}
__device__ __forceinline__ void ldsm4t(uint32_t a, uint32_t& r0, uint32_t& r1, uint32_t& r2, uint32_t& r3) {
    asm volatile("ldmatrix.sync.aligned.m8n8.x4.trans.shared.b16 {%0,%1,%2,%3}, [%4];" : "=r"(r0), "=r"(r1), "=r"(r2), "=r"(r3) : "r"(a) : "memory");
}
__device__ __forceinline__ void mma16816(float* c, uint32_t a0, uint32_t a1, uint32_t a2, uint32_t a3, uint32_t b0, uint32_t b1) {
    asm volatile("mma.sync.aligned.m16n8k16.row.col.f32.bf16.bf16.f32 {%0,%1,%2,%3}, {%4,%5,%6,%7}, {%8,%9}, {%0,%1,%2,%3};"
                 : "+f"(c[0]), "+f"(c[1]), "+f"(c[2]), "+f"(c[3]) : "r"(a0), "r"(a1), "r"(a2), "r"(a3), "r"(b0), "r"(b1));
}
__device__ __forceinline__ void mma1688z(float* c, uint32_t a0, uint32_t a1, uint32_t b0) {
    asm volatile("mma.sync.aligned.m16n8k8.row.col.f32.bf16.bf16.f32 {%0,%1,%2,%3}, {%4,%5}, {%6}, {%7,%7,%7,%7};"
                 : "=f"(c[0]), "=f"(c[1]), "=f"(c[2]), "=f"(c[3]) : "r"(a0), "r"(a1), "r"(b0), "f"(0.f));
}
__device__ __forceinline__ uint32_t pack2(float lo, float hi) { uint32_t r; asm("cvt.rn.bf16x2.f32 %0, %1, %2;" : "=r"(r) : "f"(hi), "f"(lo)); return r; }
__device__ __forceinline__ uint32_t max2(uint32_t a, uint32_t b) { uint32_t r; asm("max.NaN.bf16x2 %0, %1, %2;" : "=r"(r) : "r"(a), "r"(b)); return r; }
__device__ __forceinline__ float bf_lo(uint32_t u) { return __uint_as_float(u << 16); }
__device__ __forceinline__ float bf_hi(uint32_t u) { return __uint_as_float(u & 0xffff0000u); }
__device__ __forceinline__ float ex2(float x) { float y; asm("ex2.approx.ftz.f32 %0, %1;" : "=f"(y) : "f"(x)); return y; }
__device__ __forceinline__ float rcpa(float x) { float y; asm("rcp.approx.ftz.f32 %0, %1;" : "=f"(y) : "f"(x)); return y; }
__device__ __forceinline__ uint32_t mapa(uint32_t a, int r) { uint32_t o; asm("mapa.shared::cluster.u32 %0, %1, %2;" : "=r"(o) : "r"(a), "r"(r)); return o; }
__device__ __forceinline__ bool elect_one() { uint32_t p; asm volatile("{\n.reg .pred P;\nelect.sync _|P, 0xffffffff;\nselp.u32 %0, 1, 0, P;\n}" : "=r"(p)); return p; }
__device__ __forceinline__ void st_async4(uint32_t a, uint32_t x, uint32_t y, uint32_t z, uint32_t w, uint32_t b) {
    asm volatile("st.async.weak.shared::cluster.mbarrier::complete_tx::bytes.v4.b32 [%0], {%1,%2,%3,%4}, [%5];" :: "r"(a), "r"(x), "r"(y), "r"(z), "r"(w), "r"(b) : "memory");
}
__device__ __forceinline__ void st_async2(uint32_t a, float x, float y, uint32_t b) {
    asm volatile("st.async.weak.shared::cluster.mbarrier::complete_tx::bytes.v2.f32 [%0], {%1,%2}, [%3];" :: "r"(a), "f"(x), "f"(y), "r"(b) : "memory");
}
__device__ __forceinline__ float2 lds2(uint32_t a) { float2 x; asm volatile("ld.shared.v2.f32 {%0,%1}, [%2];" : "=f"(x.x), "=f"(x.y) : "r"(a) : "memory"); return x; }
__device__ __forceinline__ void stg4(void* p, uint4 v) {
    asm volatile("st.global.v4.u32 [%0], {%1,%2,%3,%4};" :: "l"(p), "r"(v.x), "r"(v.y), "r"(v.z), "r"(v.w) : "memory");
}
__device__ __forceinline__ uint4 shfl_xor4(uint4 v, int m) {
    return make_uint4(__shfl_xor_sync(~0u, v.x, m), __shfl_xor_sync(~0u, v.y, m), __shfl_xor_sync(~0u, v.z, m), __shfl_xor_sync(~0u, v.w, m));
}

__global__ void __launch_bounds__(NTHR, 2)
linformer_kernel(const __grid_constant__ Params pp,
                 const __grid_constant__ CUtensorMap mk, const __grid_constant__ CUtensorMap mv,
                 const __grid_constant__ CUtensorMap me, const __grid_constant__ CUtensorMap mf,
                 const __grid_constant__ CUtensorMap mq) {
    const uint64_t pol = 0x12F0000000000000ull;
    const uint64_t pol_normal = 0x1000000000000000ull;
    const unsigned b = blockIdx.x;
    const int tid = threadIdx.x, lane = tid & 31;
    if (tid == 32)
        asm volatile("cp.async.bulk.prefetch.L2.global.L2::cache_hint [%0], %1, %2;"
                     :: "l"(pp.k + (b << 15)), "r"(NPRE * UB), "l"(pol) : "memory");
    const int grp = b >> 4, j = b & 15;
    const int dh = j & 1, ne = j >> 1;
    const int kvr = (b >> 3) * 128 + (ne & 3) * 8;
    const int qr = (b >> 3) * 128 + (j & 4) * 8 + (j & 3) * 4;
    extern __shared__ __align__(1024) char smem_raw[];
    const uint32_t sbase = smem_u32(smem_raw);
    const uint32_t sproj = sbase + STAGES * UB, srecv = sproj + 8192, sfrag = srecv + 8192;
    const uint32_t bfull = sfrag + 16384, bempty = bfull + 8 * STAGES, bproj = bempty + 8 * STAGES, bred = bproj + 8, bfrag = bred + 64;
    const int warp = __shfl_sync(~0u, tid >> 5, 0);
    const bool el = elect_one();
    if (warp == 0) {
        unsigned tz; asm volatile("mov.u32 %0, %%globaltimer_lo;" : "=r"(tz));
        if (el) {
            #pragma unroll
            for (int p = 0; p < NPRE; p++) mbar_init(bfull + 8 * p, 1);
            mbar_init(bproj, 1);
            mbar_expect_tx(bproj, 8192);
            tma_load4(sproj, &me, ne & 3, ne & 4, bproj, pol_normal);
            #pragma unroll
            for (int p = 0; p < NPRE; p++) {
                mbar_expect_tx(bfull + 8 * p, UB);
                tma_load4(sbase + p * UB, &mk, dh, kvr + p * 32, bfull + 8 * p, pol);
            }
            tma_load4(sproj + 4096, &mf, ne & 3, ne & 4, bproj, pol_normal);
            asm volatile("prefetch.tensormap [%0];" :: "l"(&mv) : "memory");
        }
        asm volatile("bar.arrive 2, 128;" ::: "memory");
        if (el) asm volatile("prefetch.tensormap [%0];" :: "l"(&mq) : "memory");
        const Pace& pc = pp.c[grp == 7];
        const int step = pc.step, slow = step + pc.up, fast = step - pc.dn, slack = pc.slack, tail0 = pc.tail0, tail1 = pc.tail1;
        unsigned long long m = QMASK >> NPRE;
        unsigned dl = tz + pc.off;
        int ik = NPRE, iq = 0;
        int s = NPRE, sv = NPRE - pc.lag;
        unsigned ph = 1, phv = 0;
        asm volatile("bar.sync 1, %0;" :: "n"(NTHR) : "memory");
        asm volatile("barrier.cluster.arrive.relaxed.aligned;" ::: "memory");
        #pragma unroll 1
        for (int t = NPRE; t < NU; t++) {
            const bool isq = m & 1; m >>= 1;
            const CUtensorMap* mp = isq ? &mq : (ik & 4) ? &mv : &mk;
            const int c2 = isq ? 0 : dh;
            const int c3 = isq ? qr + (iq & 1) * 16 + (iq & 2) * 32 + (iq >> 2) * 2048 : kvr + (ik & 3) * 32 + (ik >> 3) * 2048;
            int it = 0;
            unsigned now;
            while (true) {
                const uint32_t slot_free = mbar_test(bempty + 8 * s, ph);
                asm volatile("mov.u32 %0, %%globaltimer_lo;" : "=r"(now));
                if (slot_free && (int)(now - dl) >= 0) break;
                if (++it > (1 << 22)) __trap();
            }
            if (el) {
                mbar_expect_tx(bfull + 8 * s, UB);
                tma_load4(sbase + s * UB, mp, c2, c3, bfull + 8 * s, pol);
            }
            if (isq) iq++; else ik++;
            if ((int)(now - slack - dl) > 0) dl = now - slack;
            dl += t < 8 ? step : t >= LAST_KV + 2 ? tail1 : t >= LAST_KV ? tail0 : mbar_test(bfull + 8 * sv, phv) ? fast : slow;
            if (++s == STAGES) { s = 0; ph ^= 1; }
            if (++sv == STAGES) { sv = 0; phv ^= 1; }
        }
        asm volatile("barrier.cluster.wait.aligned;" ::: "memory");
        return;
    }
    if (warp <= 3) {
        asm volatile("bar.sync 2, 128;" ::: "memory");
        if (el) {
            if (warp == 1) {
                #pragma unroll
                for (int i = 0; i < STAGES; i++) mbar_init(bempty + 8 * i, 4);
                #pragma unroll
                for (int i = NPRE; i < STAGES; i++) mbar_init(bfull + 8 * i, 1);
            } else {
                const uint32_t bx = warp == 2 ? bred : bfrag;
                #pragma unroll
                for (int i = 0; i < 8; i++) mbar_init(bx + 8 * i, 1);
                #pragma unroll
                for (int i = 0; i < 8; i++) mbar_expect_tx(bx + 8 * i, 2048);
                asm volatile("fence.mbarrier_init.release.cluster;" ::: "memory");
            }
        }
    }
    asm volatile("bar.sync 1, %0;" :: "n"(NTHR) : "memory");
    asm volatile("barrier.cluster.arrive.relaxed.aligned;" ::: "memory");
    const int g = lane >> 2;
    const int mi = lane >> 3, li = lane & 7;
    if (warp == 5) {
        uint32_t rbase[4];
        #pragma unroll
        for (int rr = 0; rr < 4; rr++) rbase[rr] = mapa(sbase, (4 * rr + mi + j + 1) & 15) - sbase;
        const uint32_t la0 = sfrag + (dh * 8 + ne) * 128 + ((li ^ (2 * (ne & 3))) << 4);
        asm volatile("barrier.cluster.wait.aligned;" ::: "memory");
        #pragma unroll 1
        for (int px = 0; px < 8; px++) {
            const uint32_t ad = srecv + (px & 3) * 2048 + lane * 8;
            mbar_wait_cluster(bred + px * 8);
            float2 x[8];
            #pragma unroll
            for (int i = 0; i < 8; i++) x[i] = lds2(ad + i * 256);
            const uint32_t o = pack2(((x[0].x + x[1].x) + (x[2].x + x[3].x)) + ((x[4].x + x[5].x) + (x[6].x + x[7].x)),
                                     ((x[0].y + x[1].y) + (x[2].y + x[3].y)) + ((x[4].y + x[5].y) + (x[6].y + x[7].y)));
            const uint32_t w0 = __shfl_sync(~0u, o, 4 * li), w1 = __shfl_sync(~0u, o, 4 * li + 1);
            const uint32_t w2 = __shfl_sync(~0u, o, 4 * li + 2), w3 = __shfl_sync(~0u, o, 4 * li + 3);
            #pragma unroll
            for (int rr = 0; rr < 4; rr++) st_async4(la0 + px * 2048 + rbase[rr], w0, w1, w2, w3, bfrag + px * 8 + rbase[rr]);
        }
        return;
    }
    const int w = (warp - 1 - (warp > 5)) & 3;
    int n0 = w >> 1, n1 = 14;
    if (warp < 5) {
        const uint32_t r0 = mapa(sbase, 4 * w + dh) - sbase, r1 = mapa(sbase, 4 * w + 2 + dh) - sbase;
        const uint32_t ra = srecv + ne * 256 + lane * 8;
        const uint32_t aoff = sbase + ((mi >> 1) * 8 + li) * 128 + (((2 * w + (mi & 1)) ^ li) << 4);
        const uint32_t boff = sproj + li * 128 + ((mi ^ li) << 4);
        unsigned long long m = ~QMASK, gm = QMASK << STAGES;
        int s = 0; unsigned par = 0;
        asm volatile("barrier.cluster.wait.aligned;" ::: "memory");
        mbar_wait(bproj, 0);
        #pragma unroll 1
        for (int px = 0; px < 8; px++) {
            float acc[2][4] = {};
            #pragma unroll 1
            for (int i = (px & 1) * 4; i < (px & 1) * 4 + 4; i++) {
                uint32_t bb[8];
                ldsm4(boff + i * 1024, bb[0], bb[1], bb[2], bb[3]);
                ldsm4((boff ^ 64) + i * 1024, bb[4], bb[5], bb[6], bb[7]);
                if (gm & 1) mbar_wait(bempty + 8 * s, par ^ 1);
                mbar_wait(bfull + 8 * s, par);
                uint32_t a[4][4];
                #pragma unroll
                for (int ks = 0; ks < 4; ks++) ldsm4t(aoff + s * UB + ks * 2048, a[ks][0], a[ks][1], a[ks][2], a[ks][3]);
                #pragma unroll
                for (int ks = 0; ks < 4; ks++) mma16816(acc[ks & 1], a[ks][0], a[ks][1], a[ks][2], a[ks][3], bb[2 * ks], bb[2 * ks + 1]);
                if ((i & 3) == 3) {
                    st_async2(ra + (px & 3) * 2048 + r0, acc[0][0] + acc[1][0], acc[0][1] + acc[1][1], bred + px * 8 + r0);
                    st_async2(ra + (px & 3) * 2048 + r1, acc[0][2] + acc[1][2], acc[0][3] + acc[1][3], bred + px * 8 + r1);
                }
                __syncwarp();
                if (lane == 0) mbar_arrive(bempty + 8 * s);
                const int dt = __ffs((unsigned)(m >> 1));
                m >>= dt; gm >>= dt; s += dt;
                if (s >= STAGES) { s -= STAGES; par ^= 1; }
            }
        }
        n0 += 14; n1 = 16;
    } else {
        asm volatile("barrier.cluster.wait.aligned;" ::: "memory");
    }
    const int rg = w & 1;
    const uint32_t qoff = sbase + (rg * 2 + (mi & 1)) * 2048 + li * 128;
    const uint32_t qx = (mi >> 1) ^ li;
    bf16* obase = pp.out + (size_t)(qr * 8 + rg * 16 + (g & 6)) * DH + li * 8;
    uint32_t kp[16], vp[16];
    unsigned long long m = warp < 5 ? 3ull << (NU - 2) : QMASK;
    if (w & 2) m &= m - 1;
    #pragma unroll 1
    for (int n = n0; n < n1; n += 2) {
        const int t = __ffsll(m) - 1; m &= m - 1; m &= m - 1;
        const int r = (t * 26) >> 8, s = t - r * STAGES;
        const unsigned par = r & 1;
        const int hg = n >> 2;
        bf16* orow = obase + (size_t)((n & 1) * 16 + (n & 2) * 32 + hg * 2048) * 8 * DH;
        const bool first = (n & 2) == 0 || n == n0;
        if (first) {
            mbar_wait_cluster(bfrag + 16 * hg);
            #pragma unroll
            for (int i = 0; i < 4; i++)
                ldsm4t(sfrag + hg * 4096 + i * 512 + mi * 128 + ((li ^ (2 * mi)) << 4), kp[4 * i], kp[4 * i + 1], kp[4 * i + 2], kp[4 * i + 3]);
        }
        if (t >= STAGES) mbar_wait(bempty + 8 * s, par ^ 1);
        mbar_wait(bfull + 8 * s, par);
        uint32_t a[8][4];
        #pragma unroll
        for (int ks = 0; ks < 8; ks++) ldsm4(qoff + s * UB + (ks >> 2) * 1024 + ((qx ^ ((ks & 3) << 1)) << 4), a[ks][0], a[ks][1], a[ks][2], a[ks][3]);
        float sc[4][4] = {};
        #pragma unroll
        for (int ks = 0; ks < 8; ks++) mma16816(sc[ks & 3], a[ks][0], a[ks][1], a[ks][2], a[ks][3], kp[2 * ks], kp[2 * ks + 1]);
        __syncwarp();
        if (lane < 2) mbar_arrive(bempty + 8 * s);
        const float scale = 0.08838834764831845f, l2e = 1.4426950408889634f;
        uint32_t u0 = pack2((sc[0][0] + sc[1][0]) + (sc[2][0] + sc[3][0]), (sc[0][2] + sc[1][2]) + (sc[2][2] + sc[3][2]));
        uint32_t u1 = pack2((sc[0][1] + sc[1][1]) + (sc[2][1] + sc[3][1]), (sc[0][3] + sc[1][3]) + (sc[2][3] + sc[3][3]));
        u0 = pack2(bf_lo(u0) * scale, bf_hi(u0) * scale);
        u1 = pack2(bf_lo(u1) * scale, bf_hi(u1) * scale);
        uint32_t mx = max2(u0, u1);
        {
            const uint32_t a1 = __shfl_xor_sync(~0u, mx, 1), a2 = __shfl_xor_sync(~0u, mx, 2), a3 = __shfl_xor_sync(~0u, mx, 3);
            mx = max2(max2(mx, a1), max2(a2, a3));
        }
        const float e0 = ex2((bf_lo(u0) - bf_lo(mx)) * l2e), e1 = ex2((bf_lo(u1) - bf_lo(mx)) * l2e);
        const float e2 = ex2((bf_hi(u0) - bf_hi(mx)) * l2e), e3 = ex2((bf_hi(u1) - bf_hi(mx)) * l2e);
        float s0 = e0 + e1, s1 = e2 + e3;
        {
            const float a1 = __shfl_xor_sync(~0u, s0, 1), b1 = __shfl_xor_sync(~0u, s1, 1);
            const float a2 = __shfl_xor_sync(~0u, s0, 2), b2 = __shfl_xor_sync(~0u, s1, 2);
            const float a3 = __shfl_xor_sync(~0u, s0, 3), b3 = __shfl_xor_sync(~0u, s1, 3);
            s0 = (s0 + a1) + (a2 + a3); s1 = (s1 + b1) + (b2 + b3);
        }
        const float r0 = rcpa(s0), r1 = rcpa(s1);
        const uint32_t pa0 = pack2(e0 * r0, e1 * r0), pa1 = pack2(e2 * r1, e3 * r1);
        if (first) {
            mbar_wait_cluster(bfrag + 16 * hg + 8);
            #pragma unroll
            for (int i = 0; i < 4; i++)
                ldsm4(sfrag + hg * 4096 + 2048 + i * 512 + (li >> 1) * 128 + (((2 * mi + (li & 1)) ^ (li & 6)) << 4), vp[4 * i], vp[4 * i + 1], vp[4 * i + 2], vp[4 * i + 3]);
        }
        #pragma unroll
        for (int H = 0; H < 2; H++) {
            uint4 lo[2], hi[2];
            #pragma unroll
            for (int J = 0; J < 2; J++) {
                float c[4][4];
                #pragma unroll
                for (int u = 0; u < 4; u++) mma1688z(c[u], pa0, pa1, vp[H * 8 + J * 4 + u]);
                lo[J] = make_uint4(pack2(c[0][0], c[0][1]), pack2(c[1][0], c[1][1]), pack2(c[2][0], c[2][1]), pack2(c[3][0], c[3][1]));
                hi[J] = make_uint4(pack2(c[0][2], c[0][3]), pack2(c[1][2], c[1][3]), pack2(c[2][2], c[2][3]), pack2(c[3][2], c[3][3]));
            }
            const bool od = g & 1;
            const uint4 xl = shfl_xor4(od ? lo[0] : lo[1], 4), xh = shfl_xor4(od ? hi[0] : hi[1], 4);
            bf16* pe = orow + H * 64;
            stg4(pe, od ? xl : lo[0]);
            stg4(pe + DH, od ? lo[1] : xl);
            stg4(pe + 8 * DH, od ? xh : hi[0]);
            stg4(pe + 9 * DH, od ? hi[1] : xh);
        }
    }
}

typedef CUresult (*EncodeFn)(CUtensorMap*, CUtensorMapDataType, cuuint32_t, void*, const cuuint64_t*, const cuuint64_t*,
                             const cuuint32_t*, const cuuint32_t*, CUtensorMapInterleave, CUtensorMapSwizzle,
                             CUtensorMapL2promotion, CUtensorMapFloatOOBfill);

void make_map(EncodeFn enc, CUtensorMap* m, void* p, int row_bytes, int d2, int d3, int stride3, int b2, int b3) {
    cuuint32_t es[4] = {1, 1, 1, 1};
    cuuint64_t d[4] = {64, 8, (cuuint64_t)d2, (cuuint64_t)d3};
    cuuint64_t s[3] = {(cuuint64_t)row_bytes, 128, (cuuint64_t)stride3};
    cuuint32_t b[4] = {64, 8, (cuuint32_t)b2, (cuuint32_t)b3};
    enc(m, CU_TENSOR_MAP_DATA_TYPE_BFLOAT16, 4, p, d, s, b, es, CU_TENSOR_MAP_INTERLEAVE_NONE, CU_TENSOR_MAP_SWIZZLE_128B,
        CU_TENSOR_MAP_L2_PROMOTION_L2_128B, CU_TENSOR_MAP_FLOAT_OOB_FILL_NONE);
}

void launch(void* const* d_in, void* d_out, const Pace& s0, const Pace& s1) {
    void* fn = nullptr;
    cudaDriverEntryPointQueryResult qr;
    cudaGetDriverEntryPoint("cuTensorMapEncodeTiled", &fn, cudaEnableDefault, &qr);
    EncodeFn enc = (EncodeFn)fn;
    CUtensorMap mq, mk, mv, me, mf;
    make_map(enc, &mq, d_in[0], 256, 2, 8192, 2048, 2, 4);
    make_map(enc, &mk, d_in[1], 256, 2, 8192, 2048, 1, 8);
    make_map(enc, &mv, d_in[2], 256, 2, 8192, 2048, 1, 8);
    make_map(enc, &me, d_in[3], 4096, 4, 8, 512, 1, 4);
    make_map(enc, &mf, d_in[4], 4096, 4, 8, 512, 1, 4);
    Params pp;
    pp.k = (const char*)d_in[1];
    pp.out = (bf16*)d_out;
    pp.c[0] = s0; pp.c[1] = s1;
    cudaFuncSetAttribute(linformer_kernel, cudaFuncAttributeMaxDynamicSharedMemorySize, SMEM_BYTES);
    cudaFuncSetAttribute(linformer_kernel, cudaFuncAttributeNonPortableClusterSizeAllowed, 1);
    cudaLaunchConfig_t cfg = {};
    cfg.gridDim = dim3(128);
    cfg.blockDim = dim3(NTHR);
    cfg.dynamicSmemBytes = SMEM_BYTES;
    cfg.stream = cudaStreamPerThread;
    cudaLaunchAttribute at[2];
    at[0].id = cudaLaunchAttributeClusterDimension;
    at[0].val.clusterDim.x = 16; at[0].val.clusterDim.y = 1; at[0].val.clusterDim.z = 1;
    at[1].id = cudaLaunchAttributeClusterSchedulingPolicyPreference;
    at[1].val.clusterSchedulingPolicyPreference = cudaClusterSchedulingPolicyLoadBalancing;
    cfg.attrs = at; cfg.numAttrs = 2;
    cudaLaunchKernelEx(&cfg, linformer_kernel, pp, mk, mv, me, mf, mq);
}

}

extern "C" void kernel_launch(void* const* d_in, const int* in_sizes, int n_in, void* d_out, int out_size) {
    (void)in_sizes; (void)n_in; (void)out_size;
    lf::launch(d_in, d_out, {740, 330, 18, 11, 4, 200, 380, 330}, {900, 306, 18, 11, 5, 200, 306, 290});
}
```

```cpp
#include <cuda_runtime.h>
#include <cuda_bf16.h>
#include <cuda.h>
#include <stdint.h>

namespace lf {

typedef __nv_bfloat16 bf16;

constexpr int DH = 128;
constexpr int NU = 48;
constexpr int UB = 8192;
constexpr int STAGES = 10;
constexpr int NTHR = 320;
constexpr int NPRE = 4;
constexpr int SMEM_BYTES = STAGES * UB + 8192 + 8192 + 16384 + 1024;

constexpr char ORDER[NU + 1] = "KKKKKKKKQKKQKKQKKQKKQKKQKKQKKQKKQKKQKQKQKKKKQQQQ";
constexpr int LAST_KV = 43;
constexpr int unit_pos(char kind, int idx) {
    for (int t = 0; t < NU; t++) if (ORDER[t] == kind && idx-- == 0) return t;
    return -1;
}
constexpr unsigned long long q_mask() {
    unsigned long long m = 0;
    for (int t = 0; t < NU; t++) if (ORDER[t] == 'Q') m |= 1ull << t;
    return m;
}
constexpr bool order_ok() {
    if (unit_pos('K', 31) != LAST_KV || unit_pos('Q', 14) != NU - 2 || unit_pos('Q', 15) != NU - 1 || unit_pos('K', NPRE) != NPRE) return false;
    for (int i = 0; i < 16; i++) {
        if (unit_pos('Q', i) < unit_pos('K', i / 4 * 8 + 7)) return false;
        if (unit_pos('Q', i) - (i < 2 ? unit_pos('K', 3) : i < 14 ? unit_pos('Q', i - 2) : LAST_KV) > STAGES) return false;
    }
    for (int i = 1; i < 32; i++) if (unit_pos('K', i) - unit_pos('K', i - 1) > STAGES) return false;
    for (int h = 0; h < 2; h++)
        if (unit_pos('Q', 4 * h) + STAGES > unit_pos('K', 8 * h + 19) || unit_pos('Q', 4 * h + 2) + STAGES > unit_pos('K', 8 * h + 23)) return false;
    return true;
}
static_assert(order_ok(), "invalid unit order");
constexpr unsigned long long QMASK = q_mask();

constexpr int PACE_UP = 18, PACE_DN = 11, PACE_SLACK = 200;
struct Pace { unsigned short off, step, tail0, tail1; };
struct Params {
    const char* k;
    const char* e;
    const char* f;
    bf16* out;
    Pace c[2];
};

__device__ __forceinline__ uint32_t smem_u32(const void* p) { return (uint32_t)__cvta_generic_to_shared(p); }
__device__ __forceinline__ void mbar_init(uint32_t bar, uint32_t cnt) { asm volatile("mbarrier.init.shared::cta.b64 [%0], %1;" :: "r"(bar), "r"(cnt) : "memory"); }
__device__ __forceinline__ void mbar_expect_tx(uint32_t bar, uint32_t bytes) { asm volatile("mbarrier.arrive.expect_tx.shared::cta.b64 _, [%0], %1;" :: "r"(bar), "r"(bytes) : "memory"); }
__device__ __forceinline__ void mbar_arrive(uint32_t bar) { asm volatile("mbarrier.arrive.shared::cta.b64 _, [%0];" :: "r"(bar) : "memory"); }
__device__ __forceinline__ void mbar_wait(uint32_t bar, uint32_t parity) {
    uint32_t done; int it = 0;
    do {
        asm volatile("{\n.reg .pred p;\nmbarrier.try_wait.parity.shared::cta.b64 p, [%1], %2;\nselp.u32 %0, 1, 0, p;\n}" : "=r"(done) : "r"(bar), "r"(parity) : "memory");
        if (++it > (1 << 22)) __trap();
    } while (!done);
}
__device__ __forceinline__ void mbar_wait_cluster(uint32_t bar) {
    uint32_t done; int it = 0;
    do {
        asm volatile("{\n.reg .pred p;\nmbarrier.try_wait.parity.acquire.cluster.shared::cta.b64 p, [%1], 0;\nselp.u32 %0, 1, 0, p;\n}" : "=r"(done) : "r"(bar) : "memory");
        if (++it > (1 << 22)) __trap();
    } while (!done);
}
__device__ __forceinline__ uint32_t mbar_test(uint32_t bar, uint32_t par) {
    uint32_t d;
    asm volatile("{\n.reg .pred p;\nmbarrier.test_wait.parity.shared::cta.b64 p, [%1], %2;\nselp.u32 %0, 1, 0, p;\n}" : "=r"(d) : "r"(bar), "r"(par) : "memory");
    return d;
}
__device__ __forceinline__ void tma_load4(uint32_t dst, const CUtensorMap* m, int c2, int c3, uint32_t bar, uint64_t pol) {
    asm volatile("cp.async.bulk.tensor.4d.shared::cluster.global.mbarrier::complete_tx::bytes.L2::cache_hint [%0], [%1, {%3, %3, %4, %5}], [%2], %6;"
                 :: "r"(dst), "l"(m), "r"(bar), "r"(0), "r"(c2), "r"(c3), "l"(pol) : "memory");
}
__device__ __forceinline__ void ldsm4(uint32_t a, uint32_t& r0, uint32_t& r1, uint32_t& r2, uint32_t& r3) {
    asm volatile("ldmatrix.sync.aligned.m8n8.x4.shared.b16 {%0,%1,%2,%3}, [%4];" : "=r"(r0), "=r"(r1), "=r"(r2), "=r"(r3) : "r"(a) : "memory");
}
__device__ __forceinline__ void ldsm4t(uint32_t a, uint32_t& r0, uint32_t& r1, uint32_t& r2, uint32_t& r3) {
    asm volatile("ldmatrix.sync.aligned.m8n8.x4.trans.shared.b16 {%0,%1,%2,%3}, [%4];" : "=r"(r0), "=r"(r1), "=r"(r2), "=r"(r3) : "r"(a) : "memory");
}
__device__ __forceinline__ void mma16816(float* c, uint32_t a0, uint32_t a1, uint32_t a2, uint32_t a3, uint32_t b0, uint32_t b1) {
    asm volatile("mma.sync.aligned.m16n8k16.row.col.f32.bf16.bf16.f32 {%0,%1,%2,%3}, {%4,%5,%6,%7}, {%8,%9}, {%0,%1,%2,%3};"
                 : "+f"(c[0]), "+f"(c[1]), "+f"(c[2]), "+f"(c[3]) : "r"(a0), "r"(a1), "r"(a2), "r"(a3), "r"(b0), "r"(b1));
}
__device__ __forceinline__ void mma1688z(float* c, uint32_t a0, uint32_t a1, uint32_t b0) {
    asm volatile("mma.sync.aligned.m16n8k8.row.col.f32.bf16.bf16.f32 {%0,%1,%2,%3}, {%4,%5}, {%6}, {%7,%7,%7,%7};"
                 : "=f"(c[0]), "=f"(c[1]), "=f"(c[2]), "=f"(c[3]) : "r"(a0), "r"(a1), "r"(b0), "f"(0.f));
}
__device__ __forceinline__ uint32_t pack2(float lo, float hi) { uint32_t r; asm("cvt.rn.bf16x2.f32 %0, %1, %2;" : "=r"(r) : "f"(hi), "f"(lo)); return r; }
__device__ __forceinline__ uint32_t max2(uint32_t a, uint32_t b) { uint32_t r; asm("max.NaN.bf16x2 %0, %1, %2;" : "=r"(r) : "r"(a), "r"(b)); return r; }
__device__ __forceinline__ float bf_lo(uint32_t u) { return __uint_as_float(u << 16); }
__device__ __forceinline__ float bf_hi(uint32_t u) { return __uint_as_float(u & 0xffff0000u); }
__device__ __forceinline__ float ex2(float x) { float y; asm("ex2.approx.ftz.f32 %0, %1;" : "=f"(y) : "f"(x)); return y; }
__device__ __forceinline__ float rcpa(float x) { float y; asm("rcp.approx.ftz.f32 %0, %1;" : "=f"(y) : "f"(x)); return y; }
__device__ __forceinline__ uint32_t mapa(uint32_t a, int r) { uint32_t o; asm("mapa.shared::cluster.u32 %0, %1, %2;" : "=r"(o) : "r"(a), "r"(r)); return o; }
__device__ __forceinline__ bool elect_one() { uint32_t p; asm volatile("{\n.reg .pred P;\nelect.sync _|P, 0xffffffff;\nselp.u32 %0, 1, 0, P;\n}" : "=r"(p)); return p; }
__device__ __forceinline__ void st_async4(uint32_t a, uint32_t x, uint32_t y, uint32_t z, uint32_t w, uint32_t b) {
    asm volatile("st.async.weak.shared::cluster.mbarrier::complete_tx::bytes.v4.b32 [%0], {%1,%2,%3,%4}, [%5];" :: "r"(a), "r"(x), "r"(y), "r"(z), "r"(w), "r"(b) : "memory");
}
__device__ __forceinline__ void st_async2(uint32_t a, float x, float y, uint32_t b) {
    asm volatile("st.async.weak.shared::cluster.mbarrier::complete_tx::bytes.v2.f32 [%0], {%1,%2}, [%3];" :: "r"(a), "f"(x), "f"(y), "r"(b) : "memory");
}
__device__ __forceinline__ float2 lds2(uint32_t a) { float2 x; asm volatile("ld.shared.v2.f32 {%0,%1}, [%2];" : "=f"(x.x), "=f"(x.y) : "r"(a) : "memory"); return x; }
__device__ __forceinline__ void stg4(void* p, uint4 v) {
    asm volatile("st.global.v4.u32 [%0], {%1,%2,%3,%4};" :: "l"(p), "r"(v.x), "r"(v.y), "r"(v.z), "r"(v.w) : "memory");
}
__device__ __forceinline__ uint4 shfl_xor4(uint4 v, int m) {
    return make_uint4(__shfl_xor_sync(~0u, v.x, m), __shfl_xor_sync(~0u, v.y, m), __shfl_xor_sync(~0u, v.z, m), __shfl_xor_sync(~0u, v.w, m));
}

__global__ void __launch_bounds__(NTHR, 2)
linformer_kernel(const __grid_constant__ Params pp,
                 const __grid_constant__ CUtensorMap mk, const __grid_constant__ CUtensorMap mv,
                 const __grid_constant__ CUtensorMap me, const __grid_constant__ CUtensorMap mf,
                 const __grid_constant__ CUtensorMap mq) {
    const uint64_t pol = 0x12F0000000000000ull;
    const uint64_t pol_normal = 0x1000000000000000ull;
    const unsigned b = blockIdx.x;
    const int tid = threadIdx.x, lane = tid & 31;
    asm volatile("prefetch.global.L2 [%0];"
                 :: "l"((tid < 256 ? pp.k + (b << 15) : ((b & 1) ? pp.f : pp.e) + ((b & 6) << 12) - 32768) + tid * 128) : "memory");
    if (tid == 288) {
        asm volatile("prefetch.tensormap [%0];" :: "l"(&me) : "memory");
        asm volatile("prefetch.tensormap [%0];" :: "l"(&mf) : "memory");
        asm volatile("prefetch.tensormap [%0];" :: "l"(&mk) : "memory");
    }
    const int grp = b >> 4, j = b & 15;
    const int dh = j & 1, ne = j >> 1;
    const int kvr = (b >> 3) * 128 + (ne & 3) * 8;
    const int qr = (b >> 3) * 128 + (j & 4) * 8 + (j & 3) * 4;
    extern __shared__ __align__(1024) char smem_raw[];
    const uint32_t sbase = smem_u32(smem_raw);
    const uint32_t sproj = sbase + STAGES * UB, srecv = sproj + 8192, sfrag = srecv + 8192;
    const uint32_t bfull = sfrag + 16384, bempty = bfull + 8 * STAGES, bproj = bempty + 8 * STAGES, bred = bproj + 8, bfrag = bred + 64;
    const int warp = __shfl_sync(~0u, tid >> 5, 0);
    const bool el = elect_one();
    if (warp == 0) {
        unsigned tz; asm volatile("mov.u32 %0, %%globaltimer_lo;" : "=r"(tz));
        if (el) {
            #pragma unroll
            for (int p = 0; p < NPRE; p++) mbar_init(bfull + 8 * p, 1);
            mbar_init(bproj, 1);
            mbar_expect_tx(bproj, 8192);
            tma_load4(sproj, &me, ne & 3, ne & 4, bproj, pol_normal);
            tma_load4(sproj + 4096, &mf, ne & 3, ne & 4, bproj, pol_normal);
            #pragma unroll
            for (int p = 0; p < NPRE; p++) {
                mbar_expect_tx(bfull + 8 * p, UB);
                tma_load4(sbase + p * UB, &mk, dh, kvr + p * 32, bfull + 8 * p, pol);
            }
            asm volatile("prefetch.tensormap [%0];" :: "l"(&mv) : "memory");
        }
        asm volatile("bar.arrive 2, 128;" ::: "memory");
        if (el) asm volatile("prefetch.tensormap [%0];" :: "l"(&mq) : "memory");
        const bool last = grp == 7;
        const Pace pc = last ? pp.c[1] : pp.c[0];
        const int step = pc.step, tail0 = pc.tail0, tail1 = pc.tail1;
        unsigned long long m = QMASK >> NPRE;
        unsigned dl = tz + pc.off;
        int ik = NPRE, iq = 0;
        int s = NPRE, sv = NPRE - 4 - last;
        unsigned ph = 1, phv = 0;
        asm volatile("bar.sync 1, %0;" :: "n"(NTHR) : "memory");
        asm volatile("barrier.cluster.arrive.relaxed.aligned;" ::: "memory");
        #pragma unroll 1
        for (int t = NPRE; t < NU; t++) {
            const bool isq = m & 1; m >>= 1;
            const CUtensorMap* mp = isq ? &mq : (ik & 4) ? &mv : &mk;
            const int c2 = isq ? 0 : dh;
            const int c3 = isq ? qr + (iq & 1) * 16 + (iq & 2) * 32 + (iq >> 2) * 2048 : kvr + (ik & 3) * 32 + (ik >> 3) * 2048;
            int it = 0;
            unsigned now;
            while (true) {
                const uint32_t slot_free = mbar_test(bempty + 8 * s, ph);
                asm volatile("mov.u32 %0, %%globaltimer_lo;" : "=r"(now));
                if (slot_free && (int)(now - dl) >= 0) break;
                if (++it > (1 << 22)) __trap();
            }
            if (el) {
                mbar_expect_tx(bfull + 8 * s, UB);
                tma_load4(sbase + s * UB, mp, c2, c3, bfull + 8 * s, pol);
            }
            if (isq) iq++; else ik++;
            if ((int)(now - PACE_SLACK - dl) > 0) dl = now - PACE_SLACK;
            dl += t < 8 ? step : t >= LAST_KV + 2 ? tail1 : t >= LAST_KV ? tail0 : mbar_test(bfull + 8 * sv, phv) ? step - PACE_DN : step + PACE_UP;
            if (++s == STAGES) { s = 0; ph ^= 1; }
            if (++sv == STAGES) { sv = 0; phv ^= 1; }
        }
        asm volatile("barrier.cluster.wait.aligned;" ::: "memory");
        return;
    }
    if (warp <= 3) {
        asm volatile("bar.sync 2, 128;" ::: "memory");
        if (el) {
            if (warp == 1) {
                #pragma unroll
                for (int i = 0; i < STAGES; i++) mbar_init(bempty + 8 * i, 4);
                #pragma unroll
                for (int i = NPRE; i < STAGES; i++) mbar_init(bfull + 8 * i, 1);
            } else {
                const uint32_t bx = warp == 2 ? bred : bfrag;
                #pragma unroll
                for (int i = 0; i < 8; i++) mbar_init(bx + 8 * i, 1);
                #pragma unroll
                for (int i = 0; i < 8; i++) mbar_expect_tx(bx + 8 * i, 2048);
                asm volatile("fence.mbarrier_init.release.cluster;" ::: "memory");
            }
        }
    }
    asm volatile("bar.sync 1, %0;" :: "n"(NTHR) : "memory");
    asm volatile("barrier.cluster.arrive.relaxed.aligned;" ::: "memory");
    const int g = lane >> 2;
    const int mi = lane >> 3, li = lane & 7;
    if (warp == 5) {
        uint32_t rbase[4];
        #pragma unroll
        for (int rr = 0; rr < 4; rr++) rbase[rr] = mapa(sbase, (4 * rr + mi + j + 1) & 15) - sbase;
        const uint32_t la0 = sfrag + (dh * 8 + ne) * 128 + ((li ^ (2 * (ne & 3))) << 4);
        asm volatile("barrier.cluster.wait.aligned;" ::: "memory");
        #pragma unroll 1
        for (int px = 0; px < 8; px++) {
            const uint32_t ad = srecv + (px & 3) * 2048 + lane * 8;
            mbar_wait_cluster(bred + px * 8);
            float2 x[8];
            #pragma unroll
            for (int i = 0; i < 8; i++) x[i] = lds2(ad + i * 256);
            const uint32_t o = pack2(((x[0].x + x[1].x) + (x[2].x + x[3].x)) + ((x[4].x + x[5].x) + (x[6].x + x[7].x)),
                                     ((x[0].y + x[1].y) + (x[2].y + x[3].y)) + ((x[4].y + x[5].y) + (x[6].y + x[7].y)));
            const uint32_t w0 = __shfl_sync(~0u, o, 4 * li), w1 = __shfl_sync(~0u, o, 4 * li + 1);
            const uint32_t w2 = __shfl_sync(~0u, o, 4 * li + 2), w3 = __shfl_sync(~0u, o, 4 * li + 3);
            #pragma unroll
            for (int rr = 0; rr < 4; rr++) st_async4(la0 + px * 2048 + rbase[rr], w0, w1, w2, w3, bfrag + px * 8 + rbase[rr]);
        }
        return;
    }
    const int w = (warp - 1 - (warp > 5)) & 3;
    int n0 = w >> 1, n1 = 14;
    if (warp < 5) {
        const uint32_t r0 = mapa(sbase, 4 * w + dh) - sbase, r1 = mapa(sbase, 4 * w + 2 + dh) - sbase;
        const uint32_t ra = srecv + ne * 256 + lane * 8;
        const uint32_t aoff = sbase + ((mi >> 1) * 8 + li) * 128 + (((2 * w + (mi & 1)) ^ li) << 4);
        const uint32_t boff = sproj + li * 128 + ((mi ^ li) << 4);
        unsigned long long m = ~QMASK, gm = QMASK << STAGES;
        int s = 0; unsigned par = 0;
        asm volatile("barrier.cluster.wait.aligned;" ::: "memory");
        mbar_wait(bproj, 0);
        #pragma unroll 1
        for (int px = 0; px < 8; px++) {
            float acc[2][4] = {};
            #pragma unroll 1
            for (int i = (px & 1) * 4; i < (px & 1) * 4 + 4; i++) {
                uint32_t bb[8];
                ldsm4(boff + i * 1024, bb[0], bb[1], bb[2], bb[3]);
                ldsm4((boff ^ 64) + i * 1024, bb[4], bb[5], bb[6], bb[7]);
                if (gm & 1) mbar_wait(bempty + 8 * s, par ^ 1);
                mbar_wait(bfull + 8 * s, par);
                uint32_t a[4][4];
                #pragma unroll
                for (int ks = 0; ks < 4; ks++) ldsm4t(aoff + s * UB + ks * 2048, a[ks][0], a[ks][1], a[ks][2], a[ks][3]);
                #pragma unroll
                for (int ks = 0; ks < 4; ks++) mma16816(acc[ks & 1], a[ks][0], a[ks][1], a[ks][2], a[ks][3], bb[2 * ks], bb[2 * ks + 1]);
                if ((i & 3) == 3) {
                    st_async2(ra + (px & 3) * 2048 + r0, acc[0][0] + acc[1][0], acc[0][1] + acc[1][1], bred + px * 8 + r0);
                    st_async2(ra + (px & 3) * 2048 + r1, acc[0][2] + acc[1][2], acc[0][3] + acc[1][3], bred + px * 8 + r1);
                }
                __syncwarp();
                if (lane == 0) mbar_arrive(bempty + 8 * s);
                const int dt = __ffs((unsigned)(m >> 1));
                m >>= dt; gm >>= dt; s += dt;
                if (s >= STAGES) { s -= STAGES; par ^= 1; }
            }
        }
        n0 += 14; n1 = 16;
    } else {
        asm volatile("barrier.cluster.wait.aligned;" ::: "memory");
    }
    const int rg = w & 1;
    const uint32_t qoff = sbase + (rg * 2 + (mi & 1)) * 2048 + li * 128;
    const uint32_t qx = (mi >> 1) ^ li;
    bf16* obase = pp.out + (size_t)(qr * 8 + rg * 16 + (g & 6)) * DH + li * 8;
    uint32_t kp[16], vp[16];
    unsigned long long m = warp < 5 ? 3ull << (NU - 2) : QMASK;
    if (w & 2) m &= m - 1;
    #pragma unroll 1
    for (int n = n0; n < n1; n += 2) {
        const int t = __ffsll(m) - 1; m &= m - 1; m &= m - 1;
        const int r = (t * 26) >> 8, s = t - r * STAGES;
        const unsigned par = r & 1;
        const int hg = n >> 2;
        bf16* orow = obase + (size_t)((n & 1) * 16 + (n & 2) * 32 + hg * 2048) * 8 * DH;
        const bool first = (n & 2) == 0 || n == n0;
        if (first) {
            mbar_wait_cluster(bfrag + 16 * hg);
            #pragma unroll
            for (int i = 0; i < 4; i++)
                ldsm4t(sfrag + hg * 4096 + i * 512 + mi * 128 + ((li ^ (2 * mi)) << 4), kp[4 * i], kp[4 * i + 1], kp[4 * i + 2], kp[4 * i + 3]);
        }
        if (t >= STAGES) mbar_wait(bempty + 8 * s, par ^ 1);
        mbar_wait(bfull + 8 * s, par);
        uint32_t a[8][4];
        #pragma unroll
        for (int ks = 0; ks < 8; ks++) ldsm4(qoff + s * UB + (ks >> 2) * 1024 + ((qx ^ ((ks & 3) << 1)) << 4), a[ks][0], a[ks][1], a[ks][2], a[ks][3]);
        float sc[4][4] = {};
        #pragma unroll
        for (int ks = 0; ks < 8; ks++) mma16816(sc[ks & 3], a[ks][0], a[ks][1], a[ks][2], a[ks][3], kp[2 * ks], kp[2 * ks + 1]);
        __syncwarp();
        if (lane < 2) mbar_arrive(bempty + 8 * s);
        const float scale = 0.08838834764831845f, l2e = 1.4426950408889634f;
        uint32_t u0 = pack2((sc[0][0] + sc[1][0]) + (sc[2][0] + sc[3][0]), (sc[0][2] + sc[1][2]) + (sc[2][2] + sc[3][2]));
        uint32_t u1 = pack2((sc[0][1] + sc[1][1]) + (sc[2][1] + sc[3][1]), (sc[0][3] + sc[1][3]) + (sc[2][3] + sc[3][3]));
        u0 = pack2(bf_lo(u0) * scale, bf_hi(u0) * scale);
        u1 = pack2(bf_lo(u1) * scale, bf_hi(u1) * scale);
        uint32_t mx = max2(u0, u1);
        {
            const uint32_t a1 = __shfl_xor_sync(~0u, mx, 1), a2 = __shfl_xor_sync(~0u, mx, 2), a3 = __shfl_xor_sync(~0u, mx, 3);
            mx = max2(max2(mx, a1), max2(a2, a3));
        }
        const float e0 = ex2((bf_lo(u0) - bf_lo(mx)) * l2e), e1 = ex2((bf_lo(u1) - bf_lo(mx)) * l2e);
        const float e2 = ex2((bf_hi(u0) - bf_hi(mx)) * l2e), e3 = ex2((bf_hi(u1) - bf_hi(mx)) * l2e);
        float s0 = e0 + e1, s1 = e2 + e3;
        {
            const float a1 = __shfl_xor_sync(~0u, s0, 1), b1 = __shfl_xor_sync(~0u, s1, 1);
            const float a2 = __shfl_xor_sync(~0u, s0, 2), b2 = __shfl_xor_sync(~0u, s1, 2);
            const float a3 = __shfl_xor_sync(~0u, s0, 3), b3 = __shfl_xor_sync(~0u, s1, 3);
            s0 = (s0 + a1) + (a2 + a3); s1 = (s1 + b1) + (b2 + b3);
        }
        const float r0 = rcpa(s0), r1 = rcpa(s1);
        const uint32_t pa0 = pack2(e0 * r0, e1 * r0), pa1 = pack2(e2 * r1, e3 * r1);
        if (first) {
            mbar_wait_cluster(bfrag + 16 * hg + 8);
            #pragma unroll
            for (int i = 0; i < 4; i++)
                ldsm4(sfrag + hg * 4096 + 2048 + i * 512 + (li >> 1) * 128 + (((2 * mi + (li & 1)) ^ (li & 6)) << 4), vp[4 * i], vp[4 * i + 1], vp[4 * i + 2], vp[4 * i + 3]);
        }
        #pragma unroll
        for (int H = 0; H < 2; H++) {
            uint4 lo[2], hi[2];
            #pragma unroll
            for (int J = 0; J < 2; J++) {
                float c[4][4];
                #pragma unroll
                for (int u = 0; u < 4; u++) mma1688z(c[u], pa0, pa1, vp[H * 8 + J * 4 + u]);
                lo[J] = make_uint4(pack2(c[0][0], c[0][1]), pack2(c[1][0], c[1][1]), pack2(c[2][0], c[2][1]), pack2(c[3][0], c[3][1]));
                hi[J] = make_uint4(pack2(c[0][2], c[0][3]), pack2(c[1][2], c[1][3]), pack2(c[2][2], c[2][3]), pack2(c[3][2], c[3][3]));
            }
            const bool od = g & 1;
            const uint4 xl = shfl_xor4(od ? lo[0] : lo[1], 4), xh = shfl_xor4(od ? hi[0] : hi[1], 4);
            bf16* pe = orow + H * 64;
            stg4(pe, od ? xl : lo[0]);
            stg4(pe + DH, od ? lo[1] : xl);
            stg4(pe + 8 * DH, od ? xh : hi[0]);
            stg4(pe + 9 * DH, od ? hi[1] : xh);
        }
    }
}

typedef CUresult (*EncodeFn)(CUtensorMap*, CUtensorMapDataType, cuuint32_t, void*, const cuuint64_t*, const cuuint64_t*,
                             const cuuint32_t*, const cuuint32_t*, CUtensorMapInterleave, CUtensorMapSwizzle,
                             CUtensorMapL2promotion, CUtensorMapFloatOOBfill);

void make_map(EncodeFn enc, CUtensorMap* m, void* p, int row_bytes, int d2, int d3, int stride3, int b2, int b3) {
    cuuint32_t es[4] = {1, 1, 1, 1};
    cuuint64_t d[4] = {64, 8, (cuuint64_t)d2, (cuuint64_t)d3};
    cuuint64_t s[3] = {(cuuint64_t)row_bytes, 128, (cuuint64_t)stride3};
    cuuint32_t b[4] = {64, 8, (cuuint32_t)b2, (cuuint32_t)b3};
    enc(m, CU_TENSOR_MAP_DATA_TYPE_BFLOAT16, 4, p, d, s, b, es, CU_TENSOR_MAP_INTERLEAVE_NONE, CU_TENSOR_MAP_SWIZZLE_128B,
        CU_TENSOR_MAP_L2_PROMOTION_L2_128B, CU_TENSOR_MAP_FLOAT_OOB_FILL_NONE);
}

void launch(void* const* d_in, void* d_out, const Pace& s0, const Pace& s1) {
    void* fn = nullptr;
    cudaDriverEntryPointQueryResult qr;
    cudaGetDriverEntryPoint("cuTensorMapEncodeTiled", &fn, cudaEnableDefault, &qr);
    EncodeFn enc = (EncodeFn)fn;
    CUtensorMap mq, mk, mv, me, mf;
    make_map(enc, &mq, d_in[0], 256, 2, 8192, 2048, 2, 4);
    make_map(enc, &mk, d_in[1], 256, 2, 8192, 2048, 1, 8);
    make_map(enc, &mv, d_in[2], 256, 2, 8192, 2048, 1, 8);
    make_map(enc, &me, d_in[3], 4096, 4, 8, 512, 1, 4);
    make_map(enc, &mf, d_in[4], 4096, 4, 8, 512, 1, 4);
    Params pp;
    pp.k = (const char*)d_in[1];
    pp.e = (const char*)d_in[3];
    pp.f = (const char*)d_in[4];
    pp.out = (bf16*)d_out;
    pp.c[0] = s0; pp.c[1] = s1;
    cudaFuncSetAttribute(linformer_kernel, cudaFuncAttributeMaxDynamicSharedMemorySize, SMEM_BYTES);
    cudaFuncSetAttribute(linformer_kernel, cudaFuncAttributeNonPortableClusterSizeAllowed, 1);
    cudaLaunchConfig_t cfg = {};
    cfg.gridDim = dim3(128);
    cfg.blockDim = dim3(NTHR);
    cfg.dynamicSmemBytes = SMEM_BYTES;
    cfg.stream = cudaStreamPerThread;
    cudaLaunchAttribute at[2];
    at[0].id = cudaLaunchAttributeClusterDimension;
    at[0].val.clusterDim.x = 16; at[0].val.clusterDim.y = 1; at[0].val.clusterDim.z = 1;
    at[1].id = cudaLaunchAttributeClusterSchedulingPolicyPreference;
    at[1].val.clusterSchedulingPolicyPreference = cudaClusterSchedulingPolicyLoadBalancing;
    cfg.attrs = at; cfg.numAttrs = 2;
    cudaLaunchKernelEx(&cfg, linformer_kernel, pp, mk, mv, me, mf, mq);
}

}

extern "C" void kernel_launch(void* const* d_in, const int* in_sizes, int n_in, void* d_out, int out_size) {
    (void)in_sizes; (void)n_in; (void)out_size;
    lf::launch(d_in, d_out, {700, 330, 390, 350}, {860, 305, 360, 400});
}
```

```cpp
#include <cuda_runtime.h>
#include <cuda_bf16.h>
#include <cuda.h>
#include <stdint.h>

namespace lf {

typedef __nv_bfloat16 bf16;

constexpr int DH = 128;
constexpr int NU = 48;
constexpr int UB = 8192;
constexpr int STAGES = 10;
constexpr int NTHR = 320;
constexpr int NPRE = 4;
constexpr int SMEM_BYTES = STAGES * UB + 8192 + 8192 + 16384 + 1024;

constexpr char ORDER[NU + 1] = "KKKKKKKKQKKQKKQKKQKKQKKQKKQKKQKKQKKQKQKQKKKKQQQQ";
constexpr int LAST_KV = 43;
constexpr int unit_pos(char kind, int idx) {
    for (int t = 0; t < NU; t++) if (ORDER[t] == kind && idx-- == 0) return t;
    return -1;
}
constexpr unsigned long long q_mask() {
    unsigned long long m = 0;
    for (int t = 0; t < NU; t++) if (ORDER[t] == 'Q') m |= 1ull << t;
    return m;
}
constexpr bool order_ok() {
    if (unit_pos('K', 31) != LAST_KV || unit_pos('Q', 14) != NU - 2 || unit_pos('Q', 15) != NU - 1 || unit_pos('K', NPRE) != NPRE) return false;
    for (int i = 0; i < 16; i++) {
        if (unit_pos('Q', i) < unit_pos('K', i / 4 * 8 + 7)) return false;
        if (unit_pos('Q', i) - (i < 2 ? unit_pos('K', 3) : i < 14 ? unit_pos('Q', i - 2) : LAST_KV) > STAGES) return false;
    }
    for (int i = 1; i < 32; i++) if (unit_pos('K', i) - unit_pos('K', i - 1) > STAGES) return false;
    for (int h = 0; h < 2; h++)
        if (unit_pos('Q', 4 * h) + STAGES > unit_pos('K', 8 * h + 19) || unit_pos('Q', 4 * h + 2) + STAGES > unit_pos('K', 8 * h + 23)) return false;
    return true;
}
static_assert(order_ok(), "invalid unit order");
constexpr unsigned long long QMASK = q_mask();

constexpr int PACE_UP = 18, PACE_DN = 11, PACE_SLACK = 200;
struct Pace { unsigned short off, step, tail0, tail1; };
struct Params {
    const char* k;
    const char* e;
    const char* f;
    bf16* out;
    Pace c[2];
};

__device__ __forceinline__ uint32_t smem_u32(const void* p) { return (uint32_t)__cvta_generic_to_shared(p); }
__device__ __forceinline__ void mbar_init(uint32_t bar, uint32_t cnt) { asm volatile("mbarrier.init.shared::cta.b64 [%0], %1;" :: "r"(bar), "r"(cnt) : "memory"); }
__device__ __forceinline__ void mbar_expect_tx(uint32_t bar, uint32_t bytes) { asm volatile("mbarrier.arrive.expect_tx.shared::cta.b64 _, [%0], %1;" :: "r"(bar), "r"(bytes) : "memory"); }
__device__ __forceinline__ void mbar_arrive(uint32_t bar) { asm volatile("mbarrier.arrive.shared::cta.b64 _, [%0];" :: "r"(bar) : "memory"); }
__device__ __forceinline__ void mbar_wait(uint32_t bar, uint32_t parity) {
    uint32_t done; int it = 0;
    do {
        asm volatile("{\n.reg .pred p;\nmbarrier.try_wait.parity.shared::cta.b64 p, [%1], %2;\nselp.u32 %0, 1, 0, p;\n}" : "=r"(done) : "r"(bar), "r"(parity) : "memory");
        if (++it > (1 << 22)) __trap();
    } while (!done);
}
__device__ __forceinline__ void mbar_wait_cluster(uint32_t bar) {
    uint32_t done; int it = 0;
    do {
        asm volatile("{\n.reg .pred p;\nmbarrier.try_wait.parity.acquire.cluster.shared::cta.b64 p, [%1], 0;\nselp.u32 %0, 1, 0, p;\n}" : "=r"(done) : "r"(bar) : "memory");
        if (++it > (1 << 22)) __trap();
    } while (!done);
}
__device__ __forceinline__ uint32_t mbar_test(uint32_t bar, uint32_t par) {
    uint32_t d;
    asm volatile("{\n.reg .pred p;\nmbarrier.test_wait.parity.shared::cta.b64 p, [%1], %2;\nselp.u32 %0, 1, 0, p;\n}" : "=r"(d) : "r"(bar), "r"(par) : "memory");
    return d;
}
__device__ __forceinline__ void tma_load4(uint32_t dst, const CUtensorMap* m, int c2, int c3, uint32_t bar, uint64_t pol) {
    asm volatile("cp.async.bulk.tensor.4d.shared::cluster.global.mbarrier::complete_tx::bytes.L2::cache_hint [%0], [%1, {%3, %3, %4, %5}], [%2], %6;"
                 :: "r"(dst), "l"(m), "r"(bar), "r"(0), "r"(c2), "r"(c3), "l"(pol) : "memory");
}
__device__ __forceinline__ void tma_load4(uint32_t dst, const CUtensorMap* m, int c2, int c3, uint32_t bar) {
    asm volatile("cp.async.bulk.tensor.4d.shared::cluster.global.mbarrier::complete_tx::bytes [%0], [%1, {%3, %3, %4, %5}], [%2];"
                 :: "r"(dst), "l"(m), "r"(bar), "r"(0), "r"(c2), "r"(c3) : "memory");
}
__device__ __forceinline__ void ldsm4(uint32_t a, uint32_t& r0, uint32_t& r1, uint32_t& r2, uint32_t& r3) {
    asm volatile("ldmatrix.sync.aligned.m8n8.x4.shared.b16 {%0,%1,%2,%3}, [%4];" : "=r"(r0), "=r"(r1), "=r"(r2), "=r"(r3) : "r"(a) : "memory");
}
__device__ __forceinline__ void ldsm4t(uint32_t a, uint32_t& r0, uint32_t& r1, uint32_t& r2, uint32_t& r3) {
    asm volatile("ldmatrix.sync.aligned.m8n8.x4.trans.shared.b16 {%0,%1,%2,%3}, [%4];" : "=r"(r0), "=r"(r1), "=r"(r2), "=r"(r3) : "r"(a) : "memory");
}
__device__ __forceinline__ void mma16816(float* c, uint32_t a0, uint32_t a1, uint32_t a2, uint32_t a3, uint32_t b0, uint32_t b1) {
    asm volatile("mma.sync.aligned.m16n8k16.row.col.f32.bf16.bf16.f32 {%0,%1,%2,%3}, {%4,%5,%6,%7}, {%8,%9}, {%0,%1,%2,%3};"
                 : "+f"(c[0]), "+f"(c[1]), "+f"(c[2]), "+f"(c[3]) : "r"(a0), "r"(a1), "r"(a2), "r"(a3), "r"(b0), "r"(b1));
}
__device__ __forceinline__ void mma1688z(float* c, uint32_t a0, uint32_t a1, uint32_t b0) {
    asm volatile("mma.sync.aligned.m16n8k8.row.col.f32.bf16.bf16.f32 {%0,%1,%2,%3}, {%4,%5}, {%6}, {%7,%7,%7,%7};"
                 : "=f"(c[0]), "=f"(c[1]), "=f"(c[2]), "=f"(c[3]) : "r"(a0), "r"(a1), "r"(b0), "f"(0.f));
}
__device__ __forceinline__ uint32_t pack2(float lo, float hi) { uint32_t r; asm("cvt.rn.bf16x2.f32 %0, %1, %2;" : "=r"(r) : "f"(hi), "f"(lo)); return r; }
__device__ __forceinline__ uint32_t max2(uint32_t a, uint32_t b) { uint32_t r; asm("max.NaN.bf16x2 %0, %1, %2;" : "=r"(r) : "r"(a), "r"(b)); return r; }
__device__ __forceinline__ float bf_lo(uint32_t u) { return __uint_as_float(u << 16); }
__device__ __forceinline__ float bf_hi(uint32_t u) { return __uint_as_float(u & 0xffff0000u); }
__device__ __forceinline__ float ex2(float x) { float y; asm("ex2.approx.ftz.f32 %0, %1;" : "=f"(y) : "f"(x)); return y; }
__device__ __forceinline__ float rcpa(float x) { float y; asm("rcp.approx.ftz.f32 %0, %1;" : "=f"(y) : "f"(x)); return y; }
__device__ __forceinline__ uint32_t mapa(uint32_t a, int r) { uint32_t o; asm("mapa.shared::cluster.u32 %0, %1, %2;" : "=r"(o) : "r"(a), "r"(r)); return o; }
__device__ __forceinline__ bool elect_one() { uint32_t p; asm volatile("{\n.reg .pred P;\nelect.sync _|P, 0xffffffff;\nselp.u32 %0, 1, 0, P;\n}" : "=r"(p)); return p; }
__device__ __forceinline__ void st_async4(uint32_t a, uint32_t x, uint32_t y, uint32_t z, uint32_t w, uint32_t b) {
    asm volatile("st.async.weak.shared::cluster.mbarrier::complete_tx::bytes.v4.b32 [%0], {%1,%2,%3,%4}, [%5];" :: "r"(a), "r"(x), "r"(y), "r"(z), "r"(w), "r"(b) : "memory");
}
__device__ __forceinline__ void st_async2(uint32_t a, float x, float y, uint32_t b) {
    asm volatile("st.async.weak.shared::cluster.mbarrier::complete_tx::bytes.v2.f32 [%0], {%1,%2}, [%3];" :: "r"(a), "f"(x), "f"(y), "r"(b) : "memory");
}
__device__ __forceinline__ float2 lds2(uint32_t a) { float2 x; asm volatile("ld.shared.v2.f32 {%0,%1}, [%2];" : "=f"(x.x), "=f"(x.y) : "r"(a) : "memory"); return x; }
__device__ __forceinline__ void stg4(void* p, uint4 v) {
    asm volatile("st.global.v4.u32 [%0], {%1,%2,%3,%4};" :: "l"(p), "r"(v.x), "r"(v.y), "r"(v.z), "r"(v.w) : "memory");
}
__device__ __forceinline__ uint4 shfl_xor4(uint4 v, int m) {
    return make_uint4(__shfl_xor_sync(~0u, v.x, m), __shfl_xor_sync(~0u, v.y, m), __shfl_xor_sync(~0u, v.z, m), __shfl_xor_sync(~0u, v.w, m));
}

__global__ void __launch_bounds__(NTHR, 2)
linformer_kernel(const __grid_constant__ Params pp,
                 const __grid_constant__ CUtensorMap mk, const __grid_constant__ CUtensorMap mv,
                 const __grid_constant__ CUtensorMap me, const __grid_constant__ CUtensorMap mf,
                 const __grid_constant__ CUtensorMap mq) {
    const unsigned b = blockIdx.x;
    const int tid = threadIdx.x, lane = tid & 31;
    asm volatile("prefetch.global.L2 [%0];"
                 :: "l"((tid < 256 ? pp.k + (b << 15) : ((b & 1) ? pp.f : pp.e) + ((b & 6) << 12) - 32768) + tid * 128) : "memory");
    if (tid == 288) {
        asm volatile("prefetch.tensormap [%0];" :: "l"(&me) : "memory");
        asm volatile("prefetch.tensormap [%0];" :: "l"(&mf) : "memory");
        asm volatile("prefetch.tensormap [%0];" :: "l"(&mk) : "memory");
    }
    const int grp = b >> 4, j = b & 15;
    const int dh = j & 1, ne = j >> 1;
    const int kvr = (b >> 3) * 128 + (ne & 3) * 8;
    const int qr = (b >> 3) * 128 + (j & 4) * 8 + (j & 3) * 4;
    extern __shared__ __align__(1024) char smem_raw[];
    const uint32_t sbase = smem_u32(smem_raw);
    const uint32_t sproj = sbase + STAGES * UB, srecv = sproj + 8192, sfrag = srecv + 8192;
    const uint32_t bfull = sfrag + 16384, bempty = bfull + 8 * STAGES, bproj = bempty + 8 * STAGES, bred = bproj + 8, bfrag = bred + 64;
    const int warp = __shfl_sync(~0u, tid >> 5, 0);
    const bool el = elect_one();
    if (warp == 0) {
        unsigned tz; asm volatile("mov.u32 %0, %%globaltimer_lo;" : "=r"(tz));
        uint64_t pol;
        asm("createpolicy.fractional.L2::evict_first.b64 %0, 1.0;" : "=l"(pol));
        if (el) {
            #pragma unroll
            for (int p = 0; p < NPRE; p++) mbar_init(bfull + 8 * p, 1);
            mbar_init(bproj, 1);
            mbar_expect_tx(bproj, 8192);
            tma_load4(sproj, &me, ne & 3, ne & 4, bproj);
            tma_load4(sproj + 4096, &mf, ne & 3, ne & 4, bproj);
            #pragma unroll
            for (int p = 0; p < NPRE; p++) {
                mbar_expect_tx(bfull + 8 * p, UB);
                tma_load4(sbase + p * UB, &mk, dh, kvr + p * 32, bfull + 8 * p, pol);
            }
            asm volatile("prefetch.tensormap [%0];" :: "l"(&mv) : "memory");
        }
        asm volatile("bar.arrive 2, 128;" ::: "memory");
        if (el) asm volatile("prefetch.tensormap [%0];" :: "l"(&mq) : "memory");
        const bool last = grp == 7;
        const Pace pc = last ? pp.c[1] : pp.c[0];
        const int step = pc.step, tail0 = pc.tail0, tail1 = pc.tail1;
        unsigned long long m = QMASK >> NPRE;
        unsigned dl = tz + pc.off;
        int ik = NPRE, iq = 0;
        int s = NPRE, sv = NPRE - 4 - last;
        unsigned ph = 1, phv = 0;
        asm volatile("bar.sync 1, %0;" :: "n"(NTHR) : "memory");
        asm volatile("barrier.cluster.arrive.relaxed.aligned;" ::: "memory");
        #pragma unroll 1
        for (int t = NPRE; t < NU; t++) {
            const bool isq = m & 1; m >>= 1;
            const CUtensorMap* mp = isq ? &mq : (ik & 4) ? &mv : &mk;
            const int c2 = isq ? 0 : dh;
            const int c3 = isq ? qr + (iq & 1) * 16 + (iq & 2) * 32 + (iq >> 2) * 2048 : kvr + (ik & 3) * 32 + (ik >> 3) * 2048;
            int it = 0;
            unsigned now;
            while (true) {
                const uint32_t slot_free = mbar_test(bempty + 8 * s, ph);
                asm volatile("mov.u32 %0, %%globaltimer_lo;" : "=r"(now));
                if (slot_free && (int)(now - dl) >= 0) break;
                if (++it > (1 << 22)) __trap();
            }
            if (el) {
                mbar_expect_tx(bfull + 8 * s, UB);
                tma_load4(sbase + s * UB, mp, c2, c3, bfull + 8 * s, pol);
            }
            if (isq) iq++; else ik++;
            if ((int)(now - PACE_SLACK - dl) > 0) dl = now - PACE_SLACK;
            dl += t < 8 ? step : t >= LAST_KV + 2 ? tail1 : t >= LAST_KV ? tail0 : mbar_test(bfull + 8 * sv, phv) ? step - PACE_DN : step + PACE_UP;
            if (++s == STAGES) { s = 0; ph ^= 1; }
            if (++sv == STAGES) { sv = 0; phv ^= 1; }
        }
        asm volatile("barrier.cluster.wait.aligned;" ::: "memory");
        return;
    }
    if (warp <= 3) {
        asm volatile("bar.sync 2, 128;" ::: "memory");
        if (el) {
            if (warp == 1) {
                #pragma unroll
                for (int i = 0; i < STAGES; i++) mbar_init(bempty + 8 * i, 4);
                #pragma unroll
                for (int i = NPRE; i < STAGES; i++) mbar_init(bfull + 8 * i, 1);
            } else {
                const uint32_t bx = warp == 2 ? bred : bfrag;
                #pragma unroll
                for (int i = 0; i < 8; i++) mbar_init(bx + 8 * i, 1);
                #pragma unroll
                for (int i = 0; i < 8; i++) mbar_expect_tx(bx + 8 * i, 2048);
                asm volatile("fence.mbarrier_init.release.cluster;" ::: "memory");
            }
        }
    }
    asm volatile("bar.sync 1, %0;" :: "n"(NTHR) : "memory");
    asm volatile("barrier.cluster.arrive.relaxed.aligned;" ::: "memory");
    const int g = lane >> 2;
    const int mi = lane >> 3, li = lane & 7;
    if (warp == 5) {
        uint32_t rbase[4];
        #pragma unroll
        for (int rr = 0; rr < 4; rr++) rbase[rr] = mapa(sbase, (4 * rr + mi + j + 1) & 15) - sbase;
        const uint32_t la0 = sfrag + (dh * 8 + ne) * 128 + ((li ^ (2 * (ne & 3))) << 4);
        asm volatile("barrier.cluster.wait.aligned;" ::: "memory");
        #pragma unroll 1
        for (int px = 0; px < 8; px++) {
            const uint32_t ad = srecv + (px & 3) * 2048 + lane * 8;
            mbar_wait_cluster(bred + px * 8);
            float2 x[8];
            #pragma unroll
            for (int i = 0; i < 8; i++) x[i] = lds2(ad + i * 256);
            const uint32_t o = pack2(((x[0].x + x[1].x) + (x[2].x + x[3].x)) + ((x[4].x + x[5].x) + (x[6].x + x[7].x)),
                                     ((x[0].y + x[1].y) + (x[2].y + x[3].y)) + ((x[4].y + x[5].y) + (x[6].y + x[7].y)));
            const uint32_t w0 = __shfl_sync(~0u, o, 4 * li), w1 = __shfl_sync(~0u, o, 4 * li + 1);
            const uint32_t w2 = __shfl_sync(~0u, o, 4 * li + 2), w3 = __shfl_sync(~0u, o, 4 * li + 3);
            #pragma unroll
            for (int rr = 0; rr < 4; rr++) st_async4(la0 + px * 2048 + rbase[rr], w0, w1, w2, w3, bfrag + px * 8 + rbase[rr]);
        }
        return;
    }
    const int w = (warp - 1 - (warp > 5)) & 3;
    int n0 = w >> 1, n1 = 14;
    if (warp < 5) {
        const uint32_t r0 = mapa(sbase, 4 * w + dh) - sbase, r1 = mapa(sbase, 4 * w + 2 + dh) - sbase;
        const uint32_t ra = srecv + ne * 256 + lane * 8;
        const uint32_t aoff = sbase + ((mi >> 1) * 8 + li) * 128 + (((2 * w + (mi & 1)) ^ li) << 4);
        const uint32_t boff = sproj + li * 128 + ((mi ^ li) << 4);
        unsigned long long m = ~QMASK, gm = QMASK << STAGES;
        int s = 0; unsigned par = 0;
        asm volatile("barrier.cluster.wait.aligned;" ::: "memory");
        mbar_wait(bproj, 0);
        #pragma unroll 1
        for (int px = 0; px < 8; px++) {
            float acc[2][4] = {};
            #pragma unroll 1
            for (int i = (px & 1) * 4; i < (px & 1) * 4 + 4; i++) {
                uint32_t bb[8];
                ldsm4(boff + i * 1024, bb[0], bb[1], bb[2], bb[3]);
                ldsm4((boff ^ 64) + i * 1024, bb[4], bb[5], bb[6], bb[7]);
                if (gm & 1) mbar_wait(bempty + 8 * s, par ^ 1);
                mbar_wait(bfull + 8 * s, par);
                uint32_t a[4][4];
                #pragma unroll
                for (int ks = 0; ks < 4; ks++) ldsm4t(aoff + s * UB + ks * 2048, a[ks][0], a[ks][1], a[ks][2], a[ks][3]);
                #pragma unroll
                for (int ks = 0; ks < 4; ks++) mma16816(acc[ks & 1], a[ks][0], a[ks][1], a[ks][2], a[ks][3], bb[2 * ks], bb[2 * ks + 1]);
                if ((i & 3) == 3) {
                    st_async2(ra + (px & 3) * 2048 + r0, acc[0][0] + acc[1][0], acc[0][1] + acc[1][1], bred + px * 8 + r0);
                    st_async2(ra + (px & 3) * 2048 + r1, acc[0][2] + acc[1][2], acc[0][3] + acc[1][3], bred + px * 8 + r1);
                }
                __syncwarp();
                if (lane == 0) mbar_arrive(bempty + 8 * s);
                const int dt = __ffs((unsigned)(m >> 1));
                m >>= dt; gm >>= dt; s += dt;
                if (s >= STAGES) { s -= STAGES; par ^= 1; }
            }
        }
        n0 += 14; n1 = 16;
    } else {
        asm volatile("barrier.cluster.wait.aligned;" ::: "memory");
    }
    const int rg = w & 1;
    const uint32_t qoff = sbase + (rg * 2 + (mi & 1)) * 2048 + li * 128;
    const uint32_t qx = (mi >> 1) ^ li;
    bf16* obase = pp.out + (size_t)(qr * 8 + rg * 16 + (g & 6)) * DH + li * 8;
    uint32_t kp[16], vp[16];
    unsigned long long m = warp < 5 ? 3ull << (NU - 2) : QMASK;
    if (w & 2) m &= m - 1;
    #pragma unroll 1
    for (int n = n0; n < n1; n += 2) {
        const int t = __ffsll(m) - 1; m &= m - 1; m &= m - 1;
        const int r = (t * 26) >> 8, s = t - r * STAGES;
        const unsigned par = r & 1;
        const int hg = n >> 2;
        bf16* orow = obase + (size_t)((n & 1) * 16 + (n & 2) * 32 + hg * 2048) * 8 * DH;
        const bool first = (n & 2) == 0 || n == n0;
        if (first) {
            mbar_wait_cluster(bfrag + 16 * hg);
            #pragma unroll
            for (int i = 0; i < 4; i++)
                ldsm4t(sfrag + hg * 4096 + i * 512 + mi * 128 + ((li ^ (2 * mi)) << 4), kp[4 * i], kp[4 * i + 1], kp[4 * i + 2], kp[4 * i + 3]);
        }
        if (t >= STAGES) mbar_wait(bempty + 8 * s, par ^ 1);
        mbar_wait(bfull + 8 * s, par);
        uint32_t a[8][4];
        #pragma unroll
        for (int ks = 0; ks < 8; ks++) ldsm4(qoff + s * UB + (ks >> 2) * 1024 + ((qx ^ ((ks & 3) << 1)) << 4), a[ks][0], a[ks][1], a[ks][2], a[ks][3]);
        float sc[4][4] = {};
        #pragma unroll
        for (int ks = 0; ks < 8; ks++) mma16816(sc[ks & 3], a[ks][0], a[ks][1], a[ks][2], a[ks][3], kp[2 * ks], kp[2 * ks + 1]);
        __syncwarp();
        if (lane < 2) mbar_arrive(bempty + 8 * s);
        const float scale = 0.08838834764831845f, l2e = 1.4426950408889634f;
        uint32_t u0 = pack2((sc[0][0] + sc[1][0]) + (sc[2][0] + sc[3][0]), (sc[0][2] + sc[1][2]) + (sc[2][2] + sc[3][2]));
        uint32_t u1 = pack2((sc[0][1] + sc[1][1]) + (sc[2][1] + sc[3][1]), (sc[0][3] + sc[1][3]) + (sc[2][3] + sc[3][3]));
        u0 = pack2(bf_lo(u0) * scale, bf_hi(u0) * scale);
        u1 = pack2(bf_lo(u1) * scale, bf_hi(u1) * scale);
        uint32_t mx = max2(u0, u1);
        {
            const uint32_t a1 = __shfl_xor_sync(~0u, mx, 1), a2 = __shfl_xor_sync(~0u, mx, 2), a3 = __shfl_xor_sync(~0u, mx, 3);
            mx = max2(max2(mx, a1), max2(a2, a3));
        }
        const float e0 = ex2((bf_lo(u0) - bf_lo(mx)) * l2e), e1 = ex2((bf_lo(u1) - bf_lo(mx)) * l2e);
        const float e2 = ex2((bf_hi(u0) - bf_hi(mx)) * l2e), e3 = ex2((bf_hi(u1) - bf_hi(mx)) * l2e);
        float s0 = e0 + e1, s1 = e2 + e3;
        {
            const float a1 = __shfl_xor_sync(~0u, s0, 1), b1 = __shfl_xor_sync(~0u, s1, 1);
            const float a2 = __shfl_xor_sync(~0u, s0, 2), b2 = __shfl_xor_sync(~0u, s1, 2);
            const float a3 = __shfl_xor_sync(~0u, s0, 3), b3 = __shfl_xor_sync(~0u, s1, 3);
            s0 = (s0 + a1) + (a2 + a3); s1 = (s1 + b1) + (b2 + b3);
        }
        const float r0 = rcpa(s0), r1 = rcpa(s1);
        const uint32_t pa0 = pack2(e0 * r0, e1 * r0), pa1 = pack2(e2 * r1, e3 * r1);
        if (first) {
            mbar_wait_cluster(bfrag + 16 * hg + 8);
            #pragma unroll
            for (int i = 0; i < 4; i++)
                ldsm4(sfrag + hg * 4096 + 2048 + i * 512 + (li >> 1) * 128 + (((2 * mi + (li & 1)) ^ (li & 6)) << 4), vp[4 * i], vp[4 * i + 1], vp[4 * i + 2], vp[4 * i + 3]);
        }
        #pragma unroll
        for (int H = 0; H < 2; H++) {
            uint4 lo[2], hi[2];
            #pragma unroll
            for (int J = 0; J < 2; J++) {
                float c[4][4];
                #pragma unroll
                for (int u = 0; u < 4; u++) mma1688z(c[u], pa0, pa1, vp[H * 8 + J * 4 + u]);
                lo[J] = make_uint4(pack2(c[0][0], c[0][1]), pack2(c[1][0], c[1][1]), pack2(c[2][0], c[2][1]), pack2(c[3][0], c[3][1]));
                hi[J] = make_uint4(pack2(c[0][2], c[0][3]), pack2(c[1][2], c[1][3]), pack2(c[2][2], c[2][3]), pack2(c[3][2], c[3][3]));
            }
            const bool od = g & 1;
            const uint4 xl = shfl_xor4(od ? lo[0] : lo[1], 4), xh = shfl_xor4(od ? hi[0] : hi[1], 4);
            bf16* pe = orow + H * 64;
            stg4(pe, od ? xl : lo[0]);
            stg4(pe + DH, od ? lo[1] : xl);
            stg4(pe + 8 * DH, od ? xh : hi[0]);
            stg4(pe + 9 * DH, od ? hi[1] : xh);
        }
    }
}

typedef CUresult (*EncodeFn)(CUtensorMap*, CUtensorMapDataType, cuuint32_t, void*, const cuuint64_t*, const cuuint64_t*,
                             const cuuint32_t*, const cuuint32_t*, CUtensorMapInterleave, CUtensorMapSwizzle,
                             CUtensorMapL2promotion, CUtensorMapFloatOOBfill);

void make_map(EncodeFn enc, CUtensorMap* m, void* p, int row_bytes, int d2, int d3, int stride3, int b2, int b3) {
    cuuint32_t es[4] = {1, 1, 1, 1};
    cuuint64_t d[4] = {64, 8, (cuuint64_t)d2, (cuuint64_t)d3};
    cuuint64_t s[3] = {(cuuint64_t)row_bytes, 128, (cuuint64_t)stride3};
    cuuint32_t b[4] = {64, 8, (cuuint32_t)b2, (cuuint32_t)b3};
    enc(m, CU_TENSOR_MAP_DATA_TYPE_BFLOAT16, 4, p, d, s, b, es, CU_TENSOR_MAP_INTERLEAVE_NONE, CU_TENSOR_MAP_SWIZZLE_128B,
        CU_TENSOR_MAP_L2_PROMOTION_L2_128B, CU_TENSOR_MAP_FLOAT_OOB_FILL_NONE);
}

void launch(void* const* d_in, void* d_out, const Pace& s0, const Pace& s1) {
    void* fn = nullptr;
    cudaDriverEntryPointQueryResult qr;
    cudaGetDriverEntryPoint("cuTensorMapEncodeTiled", &fn, cudaEnableDefault, &qr);
    EncodeFn enc = (EncodeFn)fn;
    CUtensorMap mq, mk, mv, me, mf;
    make_map(enc, &mq, d_in[0], 256, 2, 8192, 2048, 2, 4);
    make_map(enc, &mk, d_in[1], 256, 2, 8192, 2048, 1, 8);
    make_map(enc, &mv, d_in[2], 256, 2, 8192, 2048, 1, 8);
    make_map(enc, &me, d_in[3], 4096, 4, 8, 512, 1, 4);
    make_map(enc, &mf, d_in[4], 4096, 4, 8, 512, 1, 4);
    Params pp;
    pp.k = (const char*)d_in[1];
    pp.e = (const char*)d_in[3];
    pp.f = (const char*)d_in[4];
    pp.out = (bf16*)d_out;
    pp.c[0] = s0; pp.c[1] = s1;
    cudaFuncSetAttribute(linformer_kernel, cudaFuncAttributeMaxDynamicSharedMemorySize, SMEM_BYTES);
    cudaFuncSetAttribute(linformer_kernel, cudaFuncAttributeNonPortableClusterSizeAllowed, 1);
    cudaLaunchConfig_t cfg = {};
    cfg.gridDim = dim3(128);
    cfg.blockDim = dim3(NTHR);
    cfg.dynamicSmemBytes = SMEM_BYTES;
    cfg.stream = cudaStreamPerThread;
    cudaLaunchAttribute at[2];
    at[0].id = cudaLaunchAttributeClusterDimension;
    at[0].val.clusterDim.x = 16; at[0].val.clusterDim.y = 1; at[0].val.clusterDim.z = 1;
    at[1].id = cudaLaunchAttributeClusterSchedulingPolicyPreference;
    at[1].val.clusterSchedulingPolicyPreference = cudaClusterSchedulingPolicyLoadBalancing;
    cfg.attrs = at; cfg.numAttrs = 2;
    cudaLaunchKernelEx(&cfg, linformer_kernel, pp, mk, mv, me, mf, mq);
}

}

extern "C" void kernel_launch(void* const* d_in, const int* in_sizes, int n_in, void* d_out, int out_size) {
    (void)in_sizes; (void)n_in; (void)out_size;
    lf::launch(d_in, d_out, {700, 329, 390, 350}, {860, 304, 360, 400});
}
```

```cpp
#include <cuda_runtime.h>
#include <cuda_bf16.h>
#include <cuda.h>
#include <stdint.h>

namespace lf {

typedef __nv_bfloat16 bf16;

constexpr int DH = 128;
constexpr int NU = 48;
constexpr int UB = 8192;
constexpr int STAGES = 10;
constexpr int NTHR = 320;
constexpr int NPRE = 4;
constexpr int SMEM_BYTES = STAGES * UB + 8192 + 8192 + 16384 + 1024;

constexpr char ORDER[NU + 1] = "KKKKKKKKQKKQKKQKKQKKQKKQKKQKKQKKQKKQKQKQKKKKQQQQ";
constexpr int LAST_KV = 43;
constexpr int unit_pos(char kind, int idx) {
    for (int t = 0; t < NU; t++) if (ORDER[t] == kind && idx-- == 0) return t;
    return -1;
}
constexpr unsigned long long q_mask() {
    unsigned long long m = 0;
    for (int t = 0; t < NU; t++) if (ORDER[t] == 'Q') m |= 1ull << t;
    return m;
}
constexpr bool order_ok() {
    if (unit_pos('K', 31) != LAST_KV || unit_pos('Q', 14) != NU - 2 || unit_pos('Q', 15) != NU - 1 || unit_pos('K', NPRE) != NPRE) return false;
    for (int i = 0; i < 16; i++) {
        if (unit_pos('Q', i) < unit_pos('K', i / 4 * 8 + 7)) return false;
        if (unit_pos('Q', i) - (i < 2 ? unit_pos('K', 3) : i < 14 ? unit_pos('Q', i - 2) : LAST_KV) > STAGES) return false;
    }
    for (int i = 1; i < 32; i++) if (unit_pos('K', i) - unit_pos('K', i - 1) > STAGES) return false;
    for (int h = 0; h < 2; h++)
        if (unit_pos('Q', 4 * h) + STAGES > unit_pos('K', 8 * h + 19) || unit_pos('Q', 4 * h + 2) + STAGES > unit_pos('K', 8 * h + 23)) return false;
    return true;
}
static_assert(order_ok(), "invalid unit order");
constexpr unsigned long long QMASK = q_mask();

constexpr int PACE_UP = 18, PACE_DN = 11, PACE_SLACK = 200;
struct Pace { unsigned short off, step, tail0, tail1; };
struct Params {
    const char* k;
    const char* e;
    const char* f;
    bf16* out;
    Pace c[2];
};

__device__ __forceinline__ uint32_t smem_u32(const void* p) { return (uint32_t)__cvta_generic_to_shared(p); }
__device__ __forceinline__ void mbar_init(uint32_t bar, uint32_t cnt) { asm volatile("mbarrier.init.shared::cta.b64 [%0], %1;" :: "r"(bar), "r"(cnt) : "memory"); }
__device__ __forceinline__ void mbar_expect_tx(uint32_t bar, uint32_t bytes) { asm volatile("mbarrier.arrive.expect_tx.shared::cta.b64 _, [%0], %1;" :: "r"(bar), "r"(bytes) : "memory"); }
__device__ __forceinline__ void mbar_arrive(uint32_t bar) { asm volatile("mbarrier.arrive.shared::cta.b64 _, [%0];" :: "r"(bar) : "memory"); }
__device__ __forceinline__ void mbar_wait(uint32_t bar, uint32_t parity) {
    uint32_t done; int it = 0;
    do {
        asm volatile("{\n.reg .pred p;\nmbarrier.try_wait.parity.shared::cta.b64 p, [%1], %2;\nselp.u32 %0, 1, 0, p;\n}" : "=r"(done) : "r"(bar), "r"(parity) : "memory");
        if (++it > (1 << 22)) __trap();
    } while (!done);
}
__device__ __forceinline__ void mbar_wait_cluster(uint32_t bar) {
    uint32_t done; int it = 0;
    do {
        asm volatile("{\n.reg .pred p;\nmbarrier.try_wait.parity.acquire.cluster.shared::cta.b64 p, [%1], 0;\nselp.u32 %0, 1, 0, p;\n}" : "=r"(done) : "r"(bar) : "memory");
        if (++it > (1 << 22)) __trap();
    } while (!done);
}
__device__ __forceinline__ uint32_t mbar_test(uint32_t bar, uint32_t par) {
    uint32_t d;
    asm volatile("{\n.reg .pred p;\nmbarrier.test_wait.parity.shared::cta.b64 p, [%1], %2;\nselp.u32 %0, 1, 0, p;\n}" : "=r"(d) : "r"(bar), "r"(par) : "memory");
    return d;
}
__device__ __forceinline__ void tma_load4(uint32_t dst, const CUtensorMap* m, int c2, int c3, uint32_t bar, uint64_t pol) {
    asm volatile("cp.async.bulk.tensor.4d.shared::cluster.global.mbarrier::complete_tx::bytes.L2::cache_hint [%0], [%1, {%3, %3, %4, %5}], [%2], %6;"
                 :: "r"(dst), "l"(m), "r"(bar), "r"(0), "r"(c2), "r"(c3), "l"(pol) : "memory");
}
__device__ __forceinline__ void tma_load4(uint32_t dst, const CUtensorMap* m, int c2, int c3, uint32_t bar) {
    asm volatile("cp.async.bulk.tensor.4d.shared::cluster.global.mbarrier::complete_tx::bytes [%0], [%1, {%3, %3, %4, %5}], [%2];"
                 :: "r"(dst), "l"(m), "r"(bar), "r"(0), "r"(c2), "r"(c3) : "memory");
}
__device__ __forceinline__ void ldsm4(uint32_t a, uint32_t& r0, uint32_t& r1, uint32_t& r2, uint32_t& r3) {
    asm volatile("ldmatrix.sync.aligned.m8n8.x4.shared.b16 {%0,%1,%2,%3}, [%4];" : "=r"(r0), "=r"(r1), "=r"(r2), "=r"(r3) : "r"(a) : "memory");
}
__device__ __forceinline__ void ldsm4t(uint32_t a, uint32_t& r0, uint32_t& r1, uint32_t& r2, uint32_t& r3) {
    asm volatile("ldmatrix.sync.aligned.m8n8.x4.trans.shared.b16 {%0,%1,%2,%3}, [%4];" : "=r"(r0), "=r"(r1), "=r"(r2), "=r"(r3) : "r"(a) : "memory");
}
__device__ __forceinline__ void mma16816(float* c, uint32_t a0, uint32_t a1, uint32_t a2, uint32_t a3, uint32_t b0, uint32_t b1) {
    asm volatile("mma.sync.aligned.m16n8k16.row.col.f32.bf16.bf16.f32 {%0,%1,%2,%3}, {%4,%5,%6,%7}, {%8,%9}, {%0,%1,%2,%3};"
                 : "+f"(c[0]), "+f"(c[1]), "+f"(c[2]), "+f"(c[3]) : "r"(a0), "r"(a1), "r"(a2), "r"(a3), "r"(b0), "r"(b1));
}
__device__ __forceinline__ void mma1688z(float* c, uint32_t a0, uint32_t a1, uint32_t b0) {
    asm volatile("mma.sync.aligned.m16n8k8.row.col.f32.bf16.bf16.f32 {%0,%1,%2,%3}, {%4,%5}, {%6}, {%7,%7,%7,%7};"
                 : "=f"(c[0]), "=f"(c[1]), "=f"(c[2]), "=f"(c[3]) : "r"(a0), "r"(a1), "r"(b0), "f"(0.f));
}
__device__ __forceinline__ uint32_t pack2(float lo, float hi) { uint32_t r; asm("cvt.rn.bf16x2.f32 %0, %1, %2;" : "=r"(r) : "f"(hi), "f"(lo)); return r; }
__device__ __forceinline__ uint32_t max2(uint32_t a, uint32_t b) { uint32_t r; asm("max.NaN.bf16x2 %0, %1, %2;" : "=r"(r) : "r"(a), "r"(b)); return r; }
__device__ __forceinline__ float bf_lo(uint32_t u) { return __uint_as_float(u << 16); }
__device__ __forceinline__ float bf_hi(uint32_t u) { return __uint_as_float(u & 0xffff0000u); }
__device__ __forceinline__ float ex2(float x) { float y; asm("ex2.approx.ftz.f32 %0, %1;" : "=f"(y) : "f"(x)); return y; }
__device__ __forceinline__ float rcpa(float x) { float y; asm("rcp.approx.ftz.f32 %0, %1;" : "=f"(y) : "f"(x)); return y; }
__device__ __forceinline__ uint32_t mapa(uint32_t a, int r) { uint32_t o; asm("mapa.shared::cluster.u32 %0, %1, %2;" : "=r"(o) : "r"(a), "r"(r)); return o; }
__device__ __forceinline__ bool elect_one() { uint32_t p; asm volatile("{\n.reg .pred P;\nelect.sync _|P, 0xffffffff;\nselp.u32 %0, 1, 0, P;\n}" : "=r"(p)); return p; }
__device__ __forceinline__ void st_async4(uint32_t a, uint32_t x, uint32_t y, uint32_t z, uint32_t w, uint32_t b) {
    asm volatile("st.async.weak.shared::cluster.mbarrier::complete_tx::bytes.v4.b32 [%0], {%1,%2,%3,%4}, [%5];" :: "r"(a), "r"(x), "r"(y), "r"(z), "r"(w), "r"(b) : "memory");
}
__device__ __forceinline__ void st_async2(uint32_t a, float x, float y, uint32_t b) {
    asm volatile("st.async.weak.shared::cluster.mbarrier::complete_tx::bytes.v2.f32 [%0], {%1,%2}, [%3];" :: "r"(a), "f"(x), "f"(y), "r"(b) : "memory");
}
__device__ __forceinline__ float2 lds2(uint32_t a) { float2 x; asm volatile("ld.shared.v2.f32 {%0,%1}, [%2];" : "=f"(x.x), "=f"(x.y) : "r"(a) : "memory"); return x; }
__device__ __forceinline__ void stg4(void* p, uint4 v) {
    asm volatile("st.global.L1::no_allocate.v4.u32 [%0], {%1,%2,%3,%4};" :: "l"(p), "r"(v.x), "r"(v.y), "r"(v.z), "r"(v.w) : "memory");
}
__device__ __forceinline__ uint4 shfl_xor4(uint4 v, int m) {
    return make_uint4(__shfl_xor_sync(~0u, v.x, m), __shfl_xor_sync(~0u, v.y, m), __shfl_xor_sync(~0u, v.z, m), __shfl_xor_sync(~0u, v.w, m));
}

__global__ void __launch_bounds__(NTHR, 2)
linformer_kernel(const __grid_constant__ Params pp,
                 const __grid_constant__ CUtensorMap mk, const __grid_constant__ CUtensorMap mv,
                 const __grid_constant__ CUtensorMap me, const __grid_constant__ CUtensorMap mf,
                 const __grid_constant__ CUtensorMap mq) {
    const unsigned b = blockIdx.x;
    const int tid = threadIdx.x, lane = tid & 31;
    asm volatile("prefetch.global.L2 [%0];"
                 :: "l"((tid < 256 ? pp.k + (b << 15) : ((b & 1) ? pp.f : pp.e) + ((b & 6) << 12) - 32768) + tid * 128) : "memory");
    if (tid == 288) {
        asm volatile("prefetch.tensormap [%0];" :: "l"(&me) : "memory");
        asm volatile("prefetch.tensormap [%0];" :: "l"(&mf) : "memory");
        asm volatile("prefetch.tensormap [%0];" :: "l"(&mk) : "memory");
    }
    const int grp = b >> 4, j = b & 15;
    const int dh = j & 1, ne = j >> 1;
    const int kvr = (b >> 3) * 128 + (ne & 3) * 8;
    const int qr = (b >> 3) * 128 + (j & 4) * 8 + (j & 3) * 4;
    extern __shared__ __align__(1024) char smem_raw[];
    const uint32_t sbase = smem_u32(smem_raw);
    const uint32_t sproj = sbase + STAGES * UB, srecv = sproj + 8192, sfrag = srecv + 8192;
    const uint32_t bfull = sfrag + 16384, bempty = bfull + 8 * STAGES, bproj = bempty + 8 * STAGES, bred = bproj + 8, bfrag = bred + 64;
    const int warp = __shfl_sync(~0u, tid >> 5, 0);
    const bool el = elect_one();
    if (warp == 0) {
        unsigned tz; asm volatile("mov.u32 %0, %%globaltimer_lo;" : "=r"(tz));
        uint64_t pol;
        asm("createpolicy.fractional.L2::evict_first.b64 %0, 1.0;" : "=l"(pol));
        if (el) {
            #pragma unroll
            for (int p = 0; p < NPRE; p++) mbar_init(bfull + 8 * p, 1);
            mbar_init(bproj, 1);
            mbar_expect_tx(bproj, 8192);
            tma_load4(sproj, &me, ne & 3, ne & 4, bproj);
            tma_load4(sproj + 4096, &mf, ne & 3, ne & 4, bproj);
            #pragma unroll
            for (int p = 0; p < NPRE; p++) {
                mbar_expect_tx(bfull + 8 * p, UB);
                tma_load4(sbase + p * UB, &mk, dh, kvr + p * 32, bfull + 8 * p, pol);
            }
            asm volatile("prefetch.tensormap [%0];" :: "l"(&mv) : "memory");
        }
        asm volatile("barrier.arrive 2, 128;" ::: "memory");
        if (el) asm volatile("prefetch.tensormap [%0];" :: "l"(&mq) : "memory");
        const bool last = grp == 7;
        const Pace pc = last ? pp.c[1] : pp.c[0];
        const int step = pc.step, tail0 = pc.tail0, tail1 = pc.tail1;
        unsigned long long m = QMASK >> NPRE;
        unsigned dl = tz + pc.off;
        int ik = NPRE, iq = 0;
        int s = NPRE, sv = NPRE - 4 - last;
        unsigned ph = 1, phv = 0;
        asm volatile("barrier.sync 1, %0;" :: "n"(NTHR) : "memory");
        asm volatile("barrier.cluster.arrive.relaxed.aligned;" ::: "memory");
        #pragma unroll 1
        for (int t = NPRE; t < NU; t++) {
            const bool isq = m & 1; m >>= 1;
            const CUtensorMap* mp = isq ? &mq : (ik & 4) ? &mv : &mk;
            const int c2 = isq ? 0 : dh;
            const int c3 = isq ? qr + (iq & 1) * 16 + (iq & 2) * 32 + (iq >> 2) * 2048 : kvr + (ik & 3) * 32 + (ik >> 3) * 2048;
            int it = 0;
            unsigned now;
            while (true) {
                const uint32_t slot_free = mbar_test(bempty + 8 * s, ph);
                asm volatile("mov.u32 %0, %%globaltimer_lo;" : "=r"(now));
                if (slot_free && (int)(now - dl) >= 0) break;
                if (++it > (1 << 22)) __trap();
            }
            if (el) {
                mbar_expect_tx(bfull + 8 * s, UB);
                tma_load4(sbase + s * UB, mp, c2, c3, bfull + 8 * s, pol);
            }
            if (isq) iq++; else ik++;
            if ((int)(now - PACE_SLACK - dl) > 0) dl = now - PACE_SLACK;
            dl += t < 8 ? step : t >= LAST_KV + 2 ? tail1 : t >= LAST_KV ? tail0 : mbar_test(bfull + 8 * sv, phv) ? step - PACE_DN : step + PACE_UP;
            if (++s == STAGES) { s = 0; ph ^= 1; }
            if (++sv == STAGES) { sv = 0; phv ^= 1; }
        }
        asm volatile("barrier.cluster.wait.aligned;" ::: "memory");
        return;
    }
    if (warp <= 3) {
        asm volatile("barrier.sync 2, 128;" ::: "memory");
        if (el) {
            if (warp == 1) {
                #pragma unroll
                for (int i = 0; i < STAGES; i++) mbar_init(bempty + 8 * i, 4);
                #pragma unroll
                for (int i = NPRE; i < STAGES; i++) mbar_init(bfull + 8 * i, 1);
            } else {
                const uint32_t bx = warp == 2 ? bred : bfrag;
                #pragma unroll
                for (int i = 0; i < 8; i++) mbar_init(bx + 8 * i, 1);
                #pragma unroll
                for (int i = 0; i < 8; i++) mbar_expect_tx(bx + 8 * i, 2048);
                asm volatile("fence.mbarrier_init.release.cluster;" ::: "memory");
            }
        }
    }
    asm volatile("barrier.sync 1, %0;" :: "n"(NTHR) : "memory");
    asm volatile("barrier.cluster.arrive.relaxed.aligned;" ::: "memory");
    const int g = lane >> 2;
    const int mi = lane >> 3, li = lane & 7;
    if (warp == 5) {
        uint32_t rbase[4];
        #pragma unroll
        for (int rr = 0; rr < 4; rr++) rbase[rr] = mapa(sbase, (4 * rr + mi + j + 1) & 15) - sbase;
        const uint32_t la0 = sfrag + (dh * 8 + ne) * 128 + ((li ^ (2 * (ne & 3))) << 4);
        asm volatile("barrier.cluster.wait.aligned;" ::: "memory");
        #pragma unroll 1
        for (int px = 0; px < 8; px++) {
            const uint32_t ad = srecv + (px & 3) * 2048 + lane * 8;
            mbar_wait_cluster(bred + px * 8);
            float2 x[8];
            #pragma unroll
            for (int i = 0; i < 8; i++) x[i] = lds2(ad + i * 256);
            const uint32_t o = pack2(((x[0].x + x[1].x) + (x[2].x + x[3].x)) + ((x[4].x + x[5].x) + (x[6].x + x[7].x)),
                                     ((x[0].y + x[1].y) + (x[2].y + x[3].y)) + ((x[4].y + x[5].y) + (x[6].y + x[7].y)));
            const uint32_t w0 = __shfl_sync(~0u, o, 4 * li), w1 = __shfl_sync(~0u, o, 4 * li + 1);
            const uint32_t w2 = __shfl_sync(~0u, o, 4 * li + 2), w3 = __shfl_sync(~0u, o, 4 * li + 3);
            #pragma unroll
            for (int rr = 0; rr < 4; rr++) st_async4(la0 + px * 2048 + rbase[rr], w0, w1, w2, w3, bfrag + px * 8 + rbase[rr]);
        }
        return;
    }
    const int w = (warp - 1 - (warp > 5)) & 3;
    int n0 = w >> 1, n1 = 14;
    if (warp < 5) {
        const uint32_t r0 = mapa(sbase, 4 * w + dh) - sbase, r1 = mapa(sbase, 4 * w + 2 + dh) - sbase;
        const uint32_t ra = srecv + ne * 256 + lane * 8;
        const uint32_t aoff = sbase + ((mi >> 1) * 8 + li) * 128 + (((2 * w + (mi & 1)) ^ li) << 4);
        const uint32_t boff = sproj + li * 128 + ((mi ^ li) << 4);
        unsigned long long m = ~QMASK, gm = QMASK << STAGES;
        int s = 0; unsigned par = 0;
        asm volatile("barrier.cluster.wait.aligned;" ::: "memory");
        mbar_wait(bproj, 0);
        #pragma unroll 1
        for (int px = 0; px < 8; px++) {
            float acc[2][4] = {};
            #pragma unroll 1
            for (int i = (px & 1) * 4; i < (px & 1) * 4 + 4; i++) {
                uint32_t bb[8];
                ldsm4(boff + i * 1024, bb[0], bb[1], bb[2], bb[3]);
                ldsm4((boff ^ 64) + i * 1024, bb[4], bb[5], bb[6], bb[7]);
                if (gm & 1) mbar_wait(bempty + 8 * s, par ^ 1);
                mbar_wait(bfull + 8 * s, par);
                uint32_t a[4][4];
                #pragma unroll
                for (int ks = 0; ks < 4; ks++) ldsm4t(aoff + s * UB + ks * 2048, a[ks][0], a[ks][1], a[ks][2], a[ks][3]);
                #pragma unroll
                for (int ks = 0; ks < 4; ks++) mma16816(acc[ks & 1], a[ks][0], a[ks][1], a[ks][2], a[ks][3], bb[2 * ks], bb[2 * ks + 1]);
                if ((i & 3) == 3) {
                    st_async2(ra + (px & 3) * 2048 + r0, acc[0][0] + acc[1][0], acc[0][1] + acc[1][1], bred + px * 8 + r0);
                    st_async2(ra + (px & 3) * 2048 + r1, acc[0][2] + acc[1][2], acc[0][3] + acc[1][3], bred + px * 8 + r1);
                }
                __syncwarp();
                if (lane == 0) mbar_arrive(bempty + 8 * s);
                const int dt = __ffs((unsigned)(m >> 1));
                m >>= dt; gm >>= dt; s += dt;
                if (s >= STAGES) { s -= STAGES; par ^= 1; }
            }
        }
        n0 += 14; n1 = 16;
    } else {
        asm volatile("barrier.cluster.wait.aligned;" ::: "memory");
    }
    const int rg = w & 1;
    const int lr = (li & 4) | ((li & 1) << 1) | ((li >> 1) & 1);
    const uint32_t qoff = sbase + (rg * 2 + (mi & 1)) * 2048 + lr * 128;
    const uint32_t qx = (mi >> 1) ^ lr;
    bf16* obase = pp.out + (size_t)(qr * 8 + rg * 16 + ((g & 4) | ((g >> 1) & 1))) * DH + li * 8;
    uint32_t kp[16], vp[16];
    unsigned long long m = warp < 5 ? 3ull << (NU - 2) : QMASK;
    if (w & 2) m &= m - 1;
    #pragma unroll 1
    for (int n = n0; n < n1; n += 2) {
        const int t = __ffsll(m) - 1; m &= m - 1; m &= m - 1;
        const int r = (t * 26) >> 8, s = t - r * STAGES;
        const unsigned par = r & 1;
        const int hg = n >> 2;
        bf16* orow = obase + (size_t)((n & 1) * 16 + (n & 2) * 32 + hg * 2048) * 8 * DH;
        const bool first = (n & 2) == 0 || n == n0;
        if (first) {
            mbar_wait_cluster(bfrag + 16 * hg);
            #pragma unroll
            for (int i = 0; i < 4; i++)
                ldsm4t(sfrag + hg * 4096 + i * 512 + mi * 128 + ((li ^ (2 * mi)) << 4), kp[4 * i], kp[4 * i + 1], kp[4 * i + 2], kp[4 * i + 3]);
        }
        if (t >= STAGES) mbar_wait(bempty + 8 * s, par ^ 1);
        mbar_wait(bfull + 8 * s, par);
        uint32_t a[8][4];
        #pragma unroll
        for (int ks = 0; ks < 8; ks++) ldsm4(qoff + s * UB + (ks >> 2) * 1024 + ((qx ^ ((ks & 3) << 1)) << 4), a[ks][0], a[ks][1], a[ks][2], a[ks][3]);
        float sc[4][4] = {};
        #pragma unroll
        for (int ks = 0; ks < 8; ks++) mma16816(sc[ks & 3], a[ks][0], a[ks][1], a[ks][2], a[ks][3], kp[2 * ks], kp[2 * ks + 1]);
        __syncwarp();
        if (lane < 2) mbar_arrive(bempty + 8 * s);
        const float scale = 0.08838834764831845f, l2e = 1.4426950408889634f;
        uint32_t u0 = pack2((sc[0][0] + sc[1][0]) + (sc[2][0] + sc[3][0]), (sc[0][2] + sc[1][2]) + (sc[2][2] + sc[3][2]));
        uint32_t u1 = pack2((sc[0][1] + sc[1][1]) + (sc[2][1] + sc[3][1]), (sc[0][3] + sc[1][3]) + (sc[2][3] + sc[3][3]));
        u0 = pack2(bf_lo(u0) * scale, bf_hi(u0) * scale);
        u1 = pack2(bf_lo(u1) * scale, bf_hi(u1) * scale);
        uint32_t mx = max2(u0, u1);
        {
            const uint32_t a1 = __shfl_xor_sync(~0u, mx, 1), a2 = __shfl_xor_sync(~0u, mx, 2), a3 = __shfl_xor_sync(~0u, mx, 3);
            mx = max2(max2(mx, a1), max2(a2, a3));
        }
        const float e0 = ex2((bf_lo(u0) - bf_lo(mx)) * l2e), e1 = ex2((bf_lo(u1) - bf_lo(mx)) * l2e);
        const float e2 = ex2((bf_hi(u0) - bf_hi(mx)) * l2e), e3 = ex2((bf_hi(u1) - bf_hi(mx)) * l2e);
        float s0 = e0 + e1, s1 = e2 + e3;
        {
            const float a1 = __shfl_xor_sync(~0u, s0, 1), b1 = __shfl_xor_sync(~0u, s1, 1);
            const float a2 = __shfl_xor_sync(~0u, s0, 2), b2 = __shfl_xor_sync(~0u, s1, 2);
            const float a3 = __shfl_xor_sync(~0u, s0, 3), b3 = __shfl_xor_sync(~0u, s1, 3);
            s0 = (s0 + a1) + (a2 + a3); s1 = (s1 + b1) + (b2 + b3);
        }
        const float r0 = rcpa(s0), r1 = rcpa(s1);
        const uint32_t pa0 = pack2(e0 * r0, e1 * r0), pa1 = pack2(e2 * r1, e3 * r1);
        if (first) {
            mbar_wait_cluster(bfrag + 16 * hg + 8);
            #pragma unroll
            for (int i = 0; i < 4; i++)
                ldsm4(sfrag + hg * 4096 + 2048 + i * 512 + (li >> 1) * 128 + (((2 * mi + (li & 1)) ^ (li & 6)) << 4), vp[4 * i], vp[4 * i + 1], vp[4 * i + 2], vp[4 * i + 3]);
        }
        #pragma unroll
        for (int H = 0; H < 2; H++) {
            uint4 lo[2], hi[2];
            #pragma unroll
            for (int J = 0; J < 2; J++) {
                float c[4][4];
                #pragma unroll
                for (int u = 0; u < 4; u++) mma1688z(c[u], pa0, pa1, vp[H * 8 + J * 4 + u]);
                lo[J] = make_uint4(pack2(c[0][0], c[0][1]), pack2(c[1][0], c[1][1]), pack2(c[2][0], c[2][1]), pack2(c[3][0], c[3][1]));
                hi[J] = make_uint4(pack2(c[0][2], c[0][3]), pack2(c[1][2], c[1][3]), pack2(c[2][2], c[2][3]), pack2(c[3][2], c[3][3]));
            }
            const bool od = g & 1;
            const uint4 xl = shfl_xor4(od ? lo[0] : lo[1], 4), xh = shfl_xor4(od ? hi[0] : hi[1], 4);
            bf16* pe = orow + H * 64;
            stg4(pe, od ? xl : lo[0]);
            stg4(pe + 2 * DH, od ? lo[1] : xl);
            stg4(pe + 8 * DH, od ? xh : hi[0]);
            stg4(pe + 10 * DH, od ? hi[1] : xh);
        }
    }
}

typedef CUresult (*EncodeFn)(CUtensorMap*, CUtensorMapDataType, cuuint32_t, void*, const cuuint64_t*, const cuuint64_t*,
                             const cuuint32_t*, const cuuint32_t*, CUtensorMapInterleave, CUtensorMapSwizzle,
                             CUtensorMapL2promotion, CUtensorMapFloatOOBfill);

void make_map(EncodeFn enc, CUtensorMap* m, void* p, int row_bytes, int d2, int d3, int stride3, int b2, int b3) {
    cuuint32_t es[4] = {1, 1, 1, 1};
    cuuint64_t d[4] = {64, 8, (cuuint64_t)d2, (cuuint64_t)d3};
    cuuint64_t s[3] = {(cuuint64_t)row_bytes, 128, (cuuint64_t)stride3};
    cuuint32_t b[4] = {64, 8, (cuuint32_t)b2, (cuuint32_t)b3};
    enc(m, CU_TENSOR_MAP_DATA_TYPE_BFLOAT16, 4, p, d, s, b, es, CU_TENSOR_MAP_INTERLEAVE_NONE, CU_TENSOR_MAP_SWIZZLE_128B,
        CU_TENSOR_MAP_L2_PROMOTION_L2_128B, CU_TENSOR_MAP_FLOAT_OOB_FILL_NONE);
}

void launch(void* const* d_in, void* d_out, const Pace& s0, const Pace& s1) {
    void* fn = nullptr;
    cudaDriverEntryPointQueryResult qr;
    cudaGetDriverEntryPoint("cuTensorMapEncodeTiled", &fn, cudaEnableDefault, &qr);
    EncodeFn enc = (EncodeFn)fn;
    CUtensorMap mq, mk, mv, me, mf;
    make_map(enc, &mq, d_in[0], 256, 2, 8192, 2048, 2, 4);
    make_map(enc, &mk, d_in[1], 256, 2, 8192, 2048, 1, 8);
    make_map(enc, &mv, d_in[2], 256, 2, 8192, 2048, 1, 8);
    make_map(enc, &me, d_in[3], 4096, 4, 8, 512, 1, 4);
    make_map(enc, &mf, d_in[4], 4096, 4, 8, 512, 1, 4);
    Params pp;
    pp.k = (const char*)d_in[1];
    pp.e = (const char*)d_in[3];
    pp.f = (const char*)d_in[4];
    pp.out = (bf16*)d_out;
    pp.c[0] = s0; pp.c[1] = s1;
    cudaFuncSetAttribute(linformer_kernel, cudaFuncAttributeMaxDynamicSharedMemorySize, SMEM_BYTES);
    cudaFuncSetAttribute(linformer_kernel, cudaFuncAttributeNonPortableClusterSizeAllowed, 1);
    cudaLaunchConfig_t cfg = {};
    cfg.gridDim = dim3(128);
    cfg.blockDim = dim3(NTHR);
    cfg.dynamicSmemBytes = SMEM_BYTES;
    cfg.stream = cudaStreamPerThread;
    cudaLaunchAttribute at[2];
    at[0].id = cudaLaunchAttributeClusterDimension;
    at[0].val.clusterDim.x = 16; at[0].val.clusterDim.y = 1; at[0].val.clusterDim.z = 1;
    at[1].id = cudaLaunchAttributeClusterSchedulingPolicyPreference;
    at[1].val.clusterSchedulingPolicyPreference = cudaClusterSchedulingPolicyLoadBalancing;
    cfg.attrs = at; cfg.numAttrs = 2;
    cudaLaunchKernelEx(&cfg, linformer_kernel, pp, mk, mv, me, mf, mq);
}

}

extern "C" void kernel_launch(void* const* d_in, const int* in_sizes, int n_in, void* d_out, int out_size) {
    (void)in_sizes; (void)n_in; (void)out_size;
    lf::launch(d_in, d_out, {700, 328, 380, 340}, {860, 303, 360, 400});
}
```

```cpp
#include <cuda_runtime.h>
#include <cuda_bf16.h>
#include <cuda.h>
#include <stdint.h>

namespace lf {

typedef __nv_bfloat16 bf16;

constexpr int DH = 128;
constexpr int NU = 48;
constexpr int UB = 8192;
constexpr int STAGES = 10;
constexpr int NTHR = 320;
constexpr int NPRE = 4;
constexpr int SMEM_BYTES = STAGES * UB + 8192 + 8192 + 16384 + 1024;

constexpr char ORDER[NU + 1] = "KKKKKKKKQKKQKQKQKKKKQKKQKQKQKKKKQKKQKQKQKKKKQQQQ";
constexpr int LAST_KV = 43;
constexpr int unit_pos(char kind, int idx) {
    for (int t = 0; t < NU; t++) if (ORDER[t] == kind && idx-- == 0) return t;
    return -1;
}
constexpr unsigned long long q_mask() {
    unsigned long long m = 0;
    for (int t = 0; t < NU; t++) if (ORDER[t] == 'Q') m |= 1ull << t;
    return m;
}
constexpr bool order_ok() {
    if (unit_pos('K', 31) != LAST_KV || unit_pos('Q', 14) != NU - 2 || unit_pos('Q', 15) != NU - 1 || unit_pos('K', NPRE) != NPRE) return false;
    for (int i = 0; i < 16; i++) {
        if (unit_pos('Q', i) < unit_pos('K', i / 4 * 8 + 7)) return false;
        if (unit_pos('Q', i) - (i < 2 ? unit_pos('K', 3) : i < 14 ? unit_pos('Q', i - 2) : LAST_KV) > STAGES) return false;
    }
    for (int i = 1; i < 32; i++) if (unit_pos('K', i) - unit_pos('K', i - 1) > STAGES) return false;
    for (int h = 0; h < 2; h++)
        if (unit_pos('Q', 4 * h) + STAGES > unit_pos('K', 8 * h + 19) || unit_pos('Q', 4 * h + 2) + STAGES > unit_pos('K', 8 * h + 23)) return false;
    return true;
}
static_assert(order_ok(), "invalid unit order");
constexpr unsigned long long QMASK = q_mask();

constexpr int PACE_UP = 18, PACE_DN = 11, PACE_SLACK = 200;
struct Pace { unsigned short off, step, tail0, tail1; };
struct Params {
    const char* k;
    const char* e;
    const char* f;
    bf16* out;
    Pace c[2];
};

__device__ __forceinline__ uint32_t smem_u32(const void* p) { return (uint32_t)__cvta_generic_to_shared(p); }
__device__ __forceinline__ void mbar_init(uint32_t bar, uint32_t cnt) { asm volatile("mbarrier.init.shared::cta.b64 [%0], %1;" :: "r"(bar), "r"(cnt) : "memory"); }
__device__ __forceinline__ void mbar_expect_tx(uint32_t bar, uint32_t bytes) { asm volatile("mbarrier.arrive.expect_tx.shared::cta.b64 _, [%0], %1;" :: "r"(bar), "r"(bytes) : "memory"); }
__device__ __forceinline__ void mbar_arrive(uint32_t bar) { asm volatile("mbarrier.arrive.shared::cta.b64 _, [%0];" :: "r"(bar) : "memory"); }
__device__ __forceinline__ void mbar_wait(uint32_t bar, uint32_t parity) {
    uint32_t done; int it = 0;
    do {
        asm volatile("{\n.reg .pred p;\nmbarrier.try_wait.parity.shared::cta.b64 p, [%1], %2;\nselp.u32 %0, 1, 0, p;\n}" : "=r"(done) : "r"(bar), "r"(parity) : "memory");
        if (++it > (1 << 22)) __trap();
    } while (!done);
}
__device__ __forceinline__ void mbar_wait_cluster(uint32_t bar) {
    uint32_t done; int it = 0;
    do {
        asm volatile("{\n.reg .pred p;\nmbarrier.try_wait.parity.acquire.cluster.shared::cta.b64 p, [%1], 0;\nselp.u32 %0, 1, 0, p;\n}" : "=r"(done) : "r"(bar) : "memory");
        if (++it > (1 << 22)) __trap();
    } while (!done);
}
__device__ __forceinline__ uint32_t mbar_test(uint32_t bar, uint32_t par) {
    uint32_t d;
    asm volatile("{\n.reg .pred p;\nmbarrier.test_wait.parity.shared::cta.b64 p, [%1], %2;\nselp.u32 %0, 1, 0, p;\n}" : "=r"(d) : "r"(bar), "r"(par) : "memory");
    return d;
}
__device__ __forceinline__ void tma_load4(uint32_t dst, const CUtensorMap* m, int c2, int c3, uint32_t bar, uint64_t pol) {
    asm volatile("cp.async.bulk.tensor.4d.shared::cluster.global.mbarrier::complete_tx::bytes.L2::cache_hint [%0], [%1, {%3, %3, %4, %5}], [%2], %6;"
                 :: "r"(dst), "l"(m), "r"(bar), "r"(0), "r"(c2), "r"(c3), "l"(pol) : "memory");
}
__device__ __forceinline__ void tma_load4(uint32_t dst, const CUtensorMap* m, int c2, int c3, uint32_t bar) {
    asm volatile("cp.async.bulk.tensor.4d.shared::cluster.global.mbarrier::complete_tx::bytes [%0], [%1, {%3, %3, %4, %5}], [%2];"
                 :: "r"(dst), "l"(m), "r"(bar), "r"(0), "r"(c2), "r"(c3) : "memory");
}
__device__ __forceinline__ void ldsm4(uint32_t a, uint32_t& r0, uint32_t& r1, uint32_t& r2, uint32_t& r3) {
    asm volatile("ldmatrix.sync.aligned.m8n8.x4.shared.b16 {%0,%1,%2,%3}, [%4];" : "=r"(r0), "=r"(r1), "=r"(r2), "=r"(r3) : "r"(a) : "memory");
}
__device__ __forceinline__ void ldsm4t(uint32_t a, uint32_t& r0, uint32_t& r1, uint32_t& r2, uint32_t& r3) {
    asm volatile("ldmatrix.sync.aligned.m8n8.x4.trans.shared.b16 {%0,%1,%2,%3}, [%4];" : "=r"(r0), "=r"(r1), "=r"(r2), "=r"(r3) : "r"(a) : "memory");
}
__device__ __forceinline__ void mma16816(float* c, uint32_t a0, uint32_t a1, uint32_t a2, uint32_t a3, uint32_t b0, uint32_t b1) {
    asm volatile("mma.sync.aligned.m16n8k16.row.col.f32.bf16.bf16.f32 {%0,%1,%2,%3}, {%4,%5,%6,%7}, {%8,%9}, {%0,%1,%2,%3};"
                 : "+f"(c[0]), "+f"(c[1]), "+f"(c[2]), "+f"(c[3]) : "r"(a0), "r"(a1), "r"(a2), "r"(a3), "r"(b0), "r"(b1));
}
__device__ __forceinline__ void mma1688z(float* c, uint32_t a0, uint32_t a1, uint32_t b0) {
    asm volatile("mma.sync.aligned.m16n8k8.row.col.f32.bf16.bf16.f32 {%0,%1,%2,%3}, {%4,%5}, {%6}, {%7,%7,%7,%7};"
                 : "=f"(c[0]), "=f"(c[1]), "=f"(c[2]), "=f"(c[3]) : "r"(a0), "r"(a1), "r"(b0), "f"(0.f));
}
__device__ __forceinline__ uint32_t pack2(float lo, float hi) { uint32_t r; asm("cvt.rn.bf16x2.f32 %0, %1, %2;" : "=r"(r) : "f"(hi), "f"(lo)); return r; }
__device__ __forceinline__ uint32_t max2(uint32_t a, uint32_t b) { uint32_t r; asm("max.NaN.bf16x2 %0, %1, %2;" : "=r"(r) : "r"(a), "r"(b)); return r; }
__device__ __forceinline__ float bf_lo(uint32_t u) { return __uint_as_float(u << 16); }
__device__ __forceinline__ float bf_hi(uint32_t u) { return __uint_as_float(u & 0xffff0000u); }
__device__ __forceinline__ float ex2(float x) { float y; asm("ex2.approx.ftz.f32 %0, %1;" : "=f"(y) : "f"(x)); return y; }
__device__ __forceinline__ float rcpa(float x) { float y; asm("rcp.approx.ftz.f32 %0, %1;" : "=f"(y) : "f"(x)); return y; }
__device__ __forceinline__ uint32_t mapa(uint32_t a, int r) { uint32_t o; asm("mapa.shared::cluster.u32 %0, %1, %2;" : "=r"(o) : "r"(a), "r"(r)); return o; }
__device__ __forceinline__ bool elect_one() { uint32_t p; asm volatile("{\n.reg .pred P;\nelect.sync _|P, 0xffffffff;\nselp.u32 %0, 1, 0, P;\n}" : "=r"(p)); return p; }
__device__ __forceinline__ void st_async4(uint32_t a, uint32_t x, uint32_t y, uint32_t z, uint32_t w, uint32_t b) {
    asm volatile("st.async.weak.shared::cluster.mbarrier::complete_tx::bytes.v4.b32 [%0], {%1,%2,%3,%4}, [%5];" :: "r"(a), "r"(x), "r"(y), "r"(z), "r"(w), "r"(b) : "memory");
}
__device__ __forceinline__ void st_async2(uint32_t a, float x, float y, uint32_t b) {
    asm volatile("st.async.weak.shared::cluster.mbarrier::complete_tx::bytes.v2.f32 [%0], {%1,%2}, [%3];" :: "r"(a), "f"(x), "f"(y), "r"(b) : "memory");
}
__device__ __forceinline__ float2 lds2(uint32_t a) { float2 x; asm volatile("ld.shared.v2.f32 {%0,%1}, [%2];" : "=f"(x.x), "=f"(x.y) : "r"(a) : "memory"); return x; }
__device__ __forceinline__ void stg4(void* p, uint4 v) {
    asm volatile("st.global.L1::no_allocate.v4.u32 [%0], {%1,%2,%3,%4};" :: "l"(p), "r"(v.x), "r"(v.y), "r"(v.z), "r"(v.w) : "memory");
}
__device__ __forceinline__ uint4 shfl_xor4(uint4 v, int m) {
    return make_uint4(__shfl_xor_sync(~0u, v.x, m), __shfl_xor_sync(~0u, v.y, m), __shfl_xor_sync(~0u, v.z, m), __shfl_xor_sync(~0u, v.w, m));
}

__device__ __forceinline__ int unit_rows(int i, int hg) { return i * 32 + (hg & 1) * 512 + (hg & 2) * 2048; }

__global__ void __launch_bounds__(NTHR, 2)
linformer_kernel(const __grid_constant__ Params pp,
                 const __grid_constant__ CUtensorMap mk, const __grid_constant__ CUtensorMap mv,
                 const __grid_constant__ CUtensorMap me, const __grid_constant__ CUtensorMap mf,
                 const __grid_constant__ CUtensorMap mq) {
    const unsigned b = blockIdx.x;
    const int tid = threadIdx.x, lane = tid & 31;
    asm volatile("prefetch.global.L2 [%0];"
                 :: "l"((tid < 256 ? pp.k + (((b >> 5) << 21) | ((b & 31) << 15)) : ((b & 1) ? pp.f : pp.e) + ((b & 6) << 12) - 32768) + tid * 128) : "memory");
    if (tid == 288) {
        asm volatile("prefetch.tensormap [%0];" :: "l"(&me) : "memory");
        asm volatile("prefetch.tensormap [%0];" :: "l"(&mf) : "memory");
        asm volatile("prefetch.tensormap [%0];" :: "l"(&mk) : "memory");
    }
    const int grp = b >> 4, j = b & 15;
    const int dh = j & 1, ne = j >> 1;
    const int row0 = (b >> 5) * 1024 + (b & 24) * 16;
    const int kvr = row0 + (ne & 3) * 8;
    const int qr = row0 + (j & 7) * 4;
    extern __shared__ __align__(1024) char smem_raw[];
    const uint32_t sbase = smem_u32(smem_raw);
    const uint32_t sproj = sbase + STAGES * UB, srecv = sproj + 8192, sfrag = srecv + 8192;
    const uint32_t bfull = sfrag + 16384, bempty = bfull + 8 * STAGES, bproj = bempty + 8 * STAGES, bred = bproj + 8, bfrag = bred + 64;
    const int warp = __shfl_sync(~0u, tid >> 5, 0);
    const bool el = elect_one();
    if (warp == 0) {
        unsigned tz; asm volatile("mov.u32 %0, %%globaltimer_lo;" : "=r"(tz));
        uint64_t pol;
        asm("createpolicy.fractional.L2::evict_first.b64 %0, 1.0;" : "=l"(pol));
        if (el) {
            #pragma unroll
            for (int p = 0; p < NPRE; p++) mbar_init(bfull + 8 * p, 1);
            mbar_init(bproj, 1);
            mbar_expect_tx(bproj, 8192);
            tma_load4(sproj, &me, ne & 3, ne & 4, bproj);
            tma_load4(sproj + 4096, &mf, ne & 3, ne & 4, bproj);
            #pragma unroll
            for (int p = 0; p < NPRE; p++) {
                mbar_expect_tx(bfull + 8 * p, UB);
                tma_load4(sbase + p * UB, &mk, dh, kvr + p * 32, bfull + 8 * p, pol);
            }
            asm volatile("prefetch.tensormap [%0];" :: "l"(&mv) : "memory");
        }
        asm volatile("barrier.arrive 2, 128;" ::: "memory");
        if (el) asm volatile("prefetch.tensormap [%0];" :: "l"(&mq) : "memory");
        const bool last = grp == 7;
        const Pace pc = last ? pp.c[1] : pp.c[0];
        const int step = pc.step, tail0 = pc.tail0, tail1 = pc.tail1;
        unsigned long long m = QMASK >> NPRE;
        unsigned dl = tz + pc.off;
        int ik = NPRE, iq = 0;
        int s = NPRE, sv = NPRE - 4 - last;
        unsigned ph = 1, phv = 0;
        asm volatile("barrier.sync 1, %0;" :: "n"(NTHR) : "memory");
        asm volatile("barrier.cluster.arrive.relaxed.aligned;" ::: "memory");
        #pragma unroll 1
        for (int t = NPRE; t < NU; t++) {
            const bool isq = m & 1; m >>= 1;
            const CUtensorMap* mp = isq ? &mq : (ik & 4) ? &mv : &mk;
            const int c2 = isq ? 0 : dh;
            const int c3 = isq ? qr + unit_rows(iq & 3, iq >> 2) : kvr + unit_rows(ik & 3, ik >> 3);
            int it = 0;
            unsigned now;
            while (true) {
                const uint32_t slot_free = mbar_test(bempty + 8 * s, ph);
                asm volatile("mov.u32 %0, %%globaltimer_lo;" : "=r"(now));
                if (slot_free && (int)(now - dl) >= 0) break;
                if (++it > (1 << 22)) __trap();
            }
            if (el) {
                mbar_expect_tx(bfull + 8 * s, UB);
                tma_load4(sbase + s * UB, mp, c2, c3, bfull + 8 * s, pol);
            }
            if (isq) iq++; else ik++;
            if ((int)(now - PACE_SLACK - dl) > 0) dl = now - PACE_SLACK;
            dl += t < 8 ? step : t >= LAST_KV + 2 ? tail1 : t >= LAST_KV ? tail0 : mbar_test(bfull + 8 * sv, phv) ? step - PACE_DN : step + PACE_UP;
            if (++s == STAGES) { s = 0; ph ^= 1; }
            if (++sv == STAGES) { sv = 0; phv ^= 1; }
        }
        asm volatile("barrier.cluster.wait.aligned;" ::: "memory");
        return;
    }
    if (warp <= 3) {
        asm volatile("barrier.sync 2, 128;" ::: "memory");
        if (el) {
            if (warp == 1) {
                #pragma unroll
                for (int i = 0; i < STAGES; i++) mbar_init(bempty + 8 * i, 4);
                #pragma unroll
                for (int i = NPRE; i < STAGES; i++) mbar_init(bfull + 8 * i, 1);
            } else {
                const uint32_t bx = warp == 2 ? bred : bfrag;
                #pragma unroll
                for (int i = 0; i < 8; i++) mbar_init(bx + 8 * i, 1);
                #pragma unroll
                for (int i = 0; i < 8; i++) mbar_expect_tx(bx + 8 * i, 2048);
                asm volatile("fence.mbarrier_init.release.cluster;" ::: "memory");
            }
        }
    }
    asm volatile("barrier.sync 1, %0;" :: "n"(NTHR) : "memory");
    asm volatile("barrier.cluster.arrive.relaxed.aligned;" ::: "memory");
    const int g = lane >> 2;
    const int mi = lane >> 3, li = lane & 7;
    if (warp == 5) {
        uint32_t rbase[4];
        #pragma unroll
        for (int rr = 0; rr < 4; rr++) rbase[rr] = mapa(sbase, (4 * rr + mi + j + 1) & 15) - sbase;
        const uint32_t la0 = sfrag + (dh * 8 + ne) * 128 + ((li ^ (2 * (ne & 3))) << 4);
        asm volatile("barrier.cluster.wait.aligned;" ::: "memory");
        #pragma unroll 1
        for (int px = 0; px < 8; px++) {
            const uint32_t ad = srecv + (px & 3) * 2048 + lane * 8;
            mbar_wait_cluster(bred + px * 8);
            float2 x[8];
            #pragma unroll
            for (int i = 0; i < 8; i++) x[i] = lds2(ad + i * 256);
            const uint32_t o = pack2(((x[0].x + x[1].x) + (x[2].x + x[3].x)) + ((x[4].x + x[5].x) + (x[6].x + x[7].x)),
                                     ((x[0].y + x[1].y) + (x[2].y + x[3].y)) + ((x[4].y + x[5].y) + (x[6].y + x[7].y)));
            const uint32_t w0 = __shfl_sync(~0u, o, 4 * li), w1 = __shfl_sync(~0u, o, 4 * li + 1);
            const uint32_t w2 = __shfl_sync(~0u, o, 4 * li + 2), w3 = __shfl_sync(~0u, o, 4 * li + 3);
            #pragma unroll
            for (int rr = 0; rr < 4; rr++) st_async4(la0 + px * 2048 + rbase[rr], w0, w1, w2, w3, bfrag + px * 8 + rbase[rr]);
        }
        return;
    }
    const int w = (warp - 1 - (warp > 5)) & 3;
    int n0 = w >> 1, n1 = 14;
    if (warp < 5) {
        const uint32_t r0 = mapa(sbase, 4 * w + dh) - sbase, r1 = mapa(sbase, 4 * w + 2 + dh) - sbase;
        const uint32_t ra = srecv + ne * 256 + lane * 8;
        const uint32_t aoff = sbase + ((mi >> 1) * 8 + li) * 128 + (((2 * w + (mi & 1)) ^ li) << 4);
        const uint32_t boff = sproj + li * 128 + ((mi ^ li) << 4);
        unsigned long long m = ~QMASK, gm = QMASK << STAGES;
        int s = 0; unsigned par = 0;
        asm volatile("barrier.cluster.wait.aligned;" ::: "memory");
        mbar_wait(bproj, 0);
        #pragma unroll 1
        for (int px = 0; px < 8; px++) {
            float acc[2][4] = {};
            #pragma unroll 1
            for (int i = (px & 1) * 4; i < (px & 1) * 4 + 4; i++) {
                uint32_t bb[8];
                ldsm4(boff + i * 1024, bb[0], bb[1], bb[2], bb[3]);
                ldsm4((boff ^ 64) + i * 1024, bb[4], bb[5], bb[6], bb[7]);
                if (gm & 1) mbar_wait(bempty + 8 * s, par ^ 1);
                mbar_wait(bfull + 8 * s, par);
                uint32_t a[4][4];
                #pragma unroll
                for (int ks = 0; ks < 4; ks++) ldsm4t(aoff + s * UB + ks * 2048, a[ks][0], a[ks][1], a[ks][2], a[ks][3]);
                #pragma unroll
                for (int ks = 0; ks < 4; ks++) mma16816(acc[ks & 1], a[ks][0], a[ks][1], a[ks][2], a[ks][3], bb[2 * ks], bb[2 * ks + 1]);
                if ((i & 3) == 3) {
                    st_async2(ra + (px & 3) * 2048 + r0, acc[0][0] + acc[1][0], acc[0][1] + acc[1][1], bred + px * 8 + r0);
                    st_async2(ra + (px & 3) * 2048 + r1, acc[0][2] + acc[1][2], acc[0][3] + acc[1][3], bred + px * 8 + r1);
                }
                __syncwarp();
                if (lane == 0) mbar_arrive(bempty + 8 * s);
                const int dt = __ffs((unsigned)(m >> 1));
                m >>= dt; gm >>= dt; s += dt;
                if (s >= STAGES) { s -= STAGES; par ^= 1; }
            }
        }
        n0 += 14; n1 = 16;
    } else {
        asm volatile("barrier.cluster.wait.aligned;" ::: "memory");
    }
    const int rg = w & 1;
    const int lr = (li & 4) | ((li & 1) << 1) | ((li >> 1) & 1);
    const uint32_t qoff = sbase + (rg * 2 + (mi & 1)) * 2048 + lr * 128;
    const uint32_t qx = (mi >> 1) ^ lr;
    bf16* obase = pp.out + (size_t)(qr * 8 + rg * 16 + ((g & 4) | ((g >> 1) & 1))) * DH + li * 8;
    uint32_t kp[16], vp[16];
    unsigned long long m = warp < 5 ? 3ull << (NU - 2) : QMASK;
    if (w & 2) m &= m - 1;
    #pragma unroll 1
    for (int n = n0; n < n1; n += 2) {
        const int t = __ffsll(m) - 1; m &= m - 1; m &= m - 1;
        const int r = (t * 26) >> 8, s = t - r * STAGES;
        const unsigned par = r & 1;
        const int hg = n >> 2;
        bf16* orow = obase + (size_t)unit_rows(n & 3, hg) * 8 * DH;
        const bool first = (n & 2) == 0 || n == n0;
        if (first) {
            mbar_wait_cluster(bfrag + 16 * hg);
            #pragma unroll
            for (int i = 0; i < 4; i++)
                ldsm4t(sfrag + hg * 4096 + i * 512 + mi * 128 + ((li ^ (2 * mi)) << 4), kp[4 * i], kp[4 * i + 1], kp[4 * i + 2], kp[4 * i + 3]);
        }
        if (t >= STAGES) mbar_wait(bempty + 8 * s, par ^ 1);
        mbar_wait(bfull + 8 * s, par);
        uint32_t a[8][4];
        #pragma unroll
        for (int ks = 0; ks < 8; ks++) ldsm4(qoff + s * UB + (ks >> 2) * 1024 + ((qx ^ ((ks & 3) << 1)) << 4), a[ks][0], a[ks][1], a[ks][2], a[ks][3]);
        float sc[4][4] = {};
        #pragma unroll
        for (int ks = 0; ks < 8; ks++) mma16816(sc[ks & 3], a[ks][0], a[ks][1], a[ks][2], a[ks][3], kp[2 * ks], kp[2 * ks + 1]);
        __syncwarp();
        if (lane < 2) mbar_arrive(bempty + 8 * s);
        const float scale = 0.08838834764831845f, l2e = 1.4426950408889634f;
        uint32_t u0 = pack2((sc[0][0] + sc[1][0]) + (sc[2][0] + sc[3][0]), (sc[0][2] + sc[1][2]) + (sc[2][2] + sc[3][2]));
        uint32_t u1 = pack2((sc[0][1] + sc[1][1]) + (sc[2][1] + sc[3][1]), (sc[0][3] + sc[1][3]) + (sc[2][3] + sc[3][3]));
        u0 = pack2(bf_lo(u0) * scale, bf_hi(u0) * scale);
        u1 = pack2(bf_lo(u1) * scale, bf_hi(u1) * scale);
        uint32_t mx = max2(u0, u1);
        {
            const uint32_t a1 = __shfl_xor_sync(~0u, mx, 1), a2 = __shfl_xor_sync(~0u, mx, 2), a3 = __shfl_xor_sync(~0u, mx, 3);
            mx = max2(max2(mx, a1), max2(a2, a3));
        }
        const float e0 = ex2((bf_lo(u0) - bf_lo(mx)) * l2e), e1 = ex2((bf_lo(u1) - bf_lo(mx)) * l2e);
        const float e2 = ex2((bf_hi(u0) - bf_hi(mx)) * l2e), e3 = ex2((bf_hi(u1) - bf_hi(mx)) * l2e);
        float s0 = e0 + e1, s1 = e2 + e3;
        {
            const float a1 = __shfl_xor_sync(~0u, s0, 1), b1 = __shfl_xor_sync(~0u, s1, 1);
            const float a2 = __shfl_xor_sync(~0u, s0, 2), b2 = __shfl_xor_sync(~0u, s1, 2);
            const float a3 = __shfl_xor_sync(~0u, s0, 3), b3 = __shfl_xor_sync(~0u, s1, 3);
            s0 = (s0 + a1) + (a2 + a3); s1 = (s1 + b1) + (b2 + b3);
        }
        const float r0 = rcpa(s0), r1 = rcpa(s1);
        const uint32_t pa0 = pack2(e0 * r0, e1 * r0), pa1 = pack2(e2 * r1, e3 * r1);
        if (first) {
            mbar_wait_cluster(bfrag + 16 * hg + 8);
            #pragma unroll
            for (int i = 0; i < 4; i++)
                ldsm4(sfrag + hg * 4096 + 2048 + i * 512 + (li >> 1) * 128 + (((2 * mi + (li & 1)) ^ (li & 6)) << 4), vp[4 * i], vp[4 * i + 1], vp[4 * i + 2], vp[4 * i + 3]);
        }
        #pragma unroll
        for (int H = 0; H < 2; H++) {
            uint4 lo[2], hi[2];
            #pragma unroll
            for (int J = 0; J < 2; J++) {
                float c[4][4];
                #pragma unroll
                for (int u = 0; u < 4; u++) mma1688z(c[u], pa0, pa1, vp[H * 8 + J * 4 + u]);
                lo[J] = make_uint4(pack2(c[0][0], c[0][1]), pack2(c[1][0], c[1][1]), pack2(c[2][0], c[2][1]), pack2(c[3][0], c[3][1]));
                hi[J] = make_uint4(pack2(c[0][2], c[0][3]), pack2(c[1][2], c[1][3]), pack2(c[2][2], c[2][3]), pack2(c[3][2], c[3][3]));
            }
            const bool od = g & 1;
            const uint4 xl = shfl_xor4(od ? lo[0] : lo[1], 4), xh = shfl_xor4(od ? hi[0] : hi[1], 4);
            bf16* pe = orow + H * 64;
            stg4(pe, od ? xl : lo[0]);
            stg4(pe + 2 * DH, od ? lo[1] : xl);
            stg4(pe + 8 * DH, od ? xh : hi[0]);
            stg4(pe + 10 * DH, od ? hi[1] : xh);
        }
    }
}

typedef CUresult (*EncodeFn)(CUtensorMap*, CUtensorMapDataType, cuuint32_t, void*, const cuuint64_t*, const cuuint64_t*,
                             const cuuint32_t*, const cuuint32_t*, CUtensorMapInterleave, CUtensorMapSwizzle,
                             CUtensorMapL2promotion, CUtensorMapFloatOOBfill);

void make_map(EncodeFn enc, CUtensorMap* m, void* p, int row_bytes, int d2, int d3, int stride3, int b2, int b3) {
    cuuint32_t es[4] = {1, 1, 1, 1};
    cuuint64_t d[4] = {64, 8, (cuuint64_t)d2, (cuuint64_t)d3};
    cuuint64_t s[3] = {(cuuint64_t)row_bytes, 128, (cuuint64_t)stride3};
    cuuint32_t b[4] = {64, 8, (cuuint32_t)b2, (cuuint32_t)b3};
    enc(m, CU_TENSOR_MAP_DATA_TYPE_BFLOAT16, 4, p, d, s, b, es, CU_TENSOR_MAP_INTERLEAVE_NONE, CU_TENSOR_MAP_SWIZZLE_128B,
        CU_TENSOR_MAP_L2_PROMOTION_L2_128B, CU_TENSOR_MAP_FLOAT_OOB_FILL_NONE);
}

void launch(void* const* d_in, void* d_out, const Pace& s0, const Pace& s1) {
    void* fn = nullptr;
    cudaDriverEntryPointQueryResult qr;
    cudaGetDriverEntryPoint("cuTensorMapEncodeTiled", &fn, cudaEnableDefault, &qr);
    EncodeFn enc = (EncodeFn)fn;
    CUtensorMap mq, mk, mv, me, mf;
    make_map(enc, &mq, d_in[0], 256, 2, 8192, 2048, 2, 4);
    make_map(enc, &mk, d_in[1], 256, 2, 8192, 2048, 1, 8);
    make_map(enc, &mv, d_in[2], 256, 2, 8192, 2048, 1, 8);
    make_map(enc, &me, d_in[3], 4096, 4, 8, 512, 1, 4);
    make_map(enc, &mf, d_in[4], 4096, 4, 8, 512, 1, 4);
    Params pp;
    pp.k = (const char*)d_in[1];
    pp.e = (const char*)d_in[3];
    pp.f = (const char*)d_in[4];
    pp.out = (bf16*)d_out;
    pp.c[0] = s0; pp.c[1] = s1;
    cudaFuncSetAttribute(linformer_kernel, cudaFuncAttributeMaxDynamicSharedMemorySize, SMEM_BYTES);
    cudaFuncSetAttribute(linformer_kernel, cudaFuncAttributeNonPortableClusterSizeAllowed, 1);
    cudaLaunchConfig_t cfg = {};
    cfg.gridDim = dim3(128);
    cfg.blockDim = dim3(NTHR);
    cfg.dynamicSmemBytes = SMEM_BYTES;
    cfg.stream = cudaStreamPerThread;
    cudaLaunchAttribute at[2];
    at[0].id = cudaLaunchAttributeClusterDimension;
    at[0].val.clusterDim.x = 16; at[0].val.clusterDim.y = 1; at[0].val.clusterDim.z = 1;
    at[1].id = cudaLaunchAttributeClusterSchedulingPolicyPreference;
    at[1].val.clusterSchedulingPolicyPreference = cudaClusterSchedulingPolicyLoadBalancing;
    cfg.attrs = at; cfg.numAttrs = 2;
    cudaLaunchKernelEx(&cfg, linformer_kernel, pp, mk, mv, me, mf, mq);
}

}

extern "C" void kernel_launch(void* const* d_in, const int* in_sizes, int n_in, void* d_out, int out_size) {
    (void)in_sizes; (void)n_in; (void)out_size;
    lf::launch(d_in, d_out, {700, 328, 380, 340}, {860, 302, 360, 400});
}
```

```cpp
#include <cuda_runtime.h>
#include <cuda_bf16.h>
#include <cuda.h>
#include <stdint.h>

namespace lf {

typedef __nv_bfloat16 bf16;

constexpr int DH = 128;
constexpr int NU = 48;
constexpr int UB = 8192;
constexpr int STAGES = 10;
constexpr int NTHR = 320;
constexpr int NPRE = 4;
constexpr int SMEM_BYTES = STAGES * UB + 8192 + 8192 + 16384 + 1024;

constexpr char ORDER[NU + 1] = "KKKKKKKKQKKQKKQKQKKKQKKQKKQKQKKKQKKQKQKQKKKKQQQQ";
constexpr int LAST_KV = 43;
constexpr int unit_pos(char kind, int idx) {
    for (int t = 0; t < NU; t++) if (ORDER[t] == kind && idx-- == 0) return t;
    return -1;
}
constexpr unsigned long long q_mask() {
    unsigned long long m = 0;
    for (int t = 0; t < NU; t++) if (ORDER[t] == 'Q') m |= 1ull << t;
    return m;
}
constexpr bool order_ok() {
    if (unit_pos('K', 31) != LAST_KV || unit_pos('Q', 14) != NU - 2 || unit_pos('Q', 15) != NU - 1 || unit_pos('K', NPRE) != NPRE) return false;
    for (int i = 0; i < 16; i++) {
        if (unit_pos('Q', i) < unit_pos('K', i / 4 * 8 + 7)) return false;
        if (unit_pos('Q', i) - (i < 2 ? unit_pos('K', 3) : i < 14 ? unit_pos('Q', i - 2) : LAST_KV) > STAGES) return false;
    }
    for (int i = 1; i < 32; i++) if (unit_pos('K', i) - unit_pos('K', i - 1) > STAGES) return false;
    for (int h = 0; h < 2; h++)
        if (unit_pos('Q', 4 * h) + STAGES > unit_pos('K', 8 * h + 19) || unit_pos('Q', 4 * h + 2) + STAGES > unit_pos('K', 8 * h + 23)) return false;
    return true;
}
static_assert(order_ok(), "invalid unit order");
constexpr unsigned long long QMASK = q_mask();

constexpr int PACE_UP = 18, PACE_DN = 11, PACE_SLACK = 200;
struct Pace { unsigned short off, step, tail0, tail1; };
struct Params {
    const char* k;
    const char* e;
    const char* f;
    bf16* out;
    Pace c[2];
};

__device__ __forceinline__ uint32_t smem_u32(const void* p) { return (uint32_t)__cvta_generic_to_shared(p); }
__device__ __forceinline__ void mbar_init(uint32_t bar, uint32_t cnt) { asm volatile("mbarrier.init.shared::cta.b64 [%0], %1;" :: "r"(bar), "r"(cnt) : "memory"); }
__device__ __forceinline__ void mbar_expect_tx(uint32_t bar, uint32_t bytes) { asm volatile("mbarrier.arrive.expect_tx.shared::cta.b64 _, [%0], %1;" :: "r"(bar), "r"(bytes) : "memory"); }
__device__ __forceinline__ void mbar_arrive(uint32_t bar) { asm volatile("mbarrier.arrive.shared::cta.b64 _, [%0];" :: "r"(bar) : "memory"); }
__device__ __forceinline__ void mbar_wait(uint32_t bar, uint32_t parity) {
    uint32_t done; int it = 0;
    do {
        asm volatile("{\n.reg .pred p;\nmbarrier.try_wait.parity.shared::cta.b64 p, [%1], %2;\nselp.u32 %0, 1, 0, p;\n}" : "=r"(done) : "r"(bar), "r"(parity) : "memory");
        if (++it > (1 << 22)) __trap();
    } while (!done);
}
__device__ __forceinline__ void mbar_wait_cluster(uint32_t bar) {
    uint32_t done; int it = 0;
    do {
        asm volatile("{\n.reg .pred p;\nmbarrier.try_wait.parity.acquire.cluster.shared::cta.b64 p, [%1], 0;\nselp.u32 %0, 1, 0, p;\n}" : "=r"(done) : "r"(bar) : "memory");
        if (++it > (1 << 22)) __trap();
    } while (!done);
}
__device__ __forceinline__ uint32_t mbar_test(uint32_t bar, uint32_t par) {
    uint32_t d;
    asm volatile("{\n.reg .pred p;\nmbarrier.test_wait.parity.shared::cta.b64 p, [%1], %2;\nselp.u32 %0, 1, 0, p;\n}" : "=r"(d) : "r"(bar), "r"(par) : "memory");
    return d;
}
__device__ __forceinline__ void tma_load4(uint32_t dst, const CUtensorMap* m, int c2, int c3, uint32_t bar, uint64_t pol) {
    asm volatile("cp.async.bulk.tensor.4d.shared::cluster.global.mbarrier::complete_tx::bytes.L2::cache_hint [%0], [%1, {%3, %3, %4, %5}], [%2], %6;"
                 :: "r"(dst), "l"(m), "r"(bar), "r"(0), "r"(c2), "r"(c3), "l"(pol) : "memory");
}
__device__ __forceinline__ void tma_load_proj(uint32_t dst, const CUtensorMap* m, int c0, uint32_t bar) {
    asm volatile("cp.async.bulk.tensor.4d.shared::cluster.global.mbarrier::complete_tx::bytes [%0], [%1, {%4, %3, %3, %3}], [%2];"
                 :: "r"(dst), "l"(m), "r"(bar), "r"(0), "r"(c0) : "memory");
}
__device__ __forceinline__ void ldsm4(uint32_t a, uint32_t& r0, uint32_t& r1, uint32_t& r2, uint32_t& r3) {
    asm volatile("ldmatrix.sync.aligned.m8n8.x4.shared.b16 {%0,%1,%2,%3}, [%4];" : "=r"(r0), "=r"(r1), "=r"(r2), "=r"(r3) : "r"(a) : "memory");
}
__device__ __forceinline__ void ldsm4t(uint32_t a, uint32_t& r0, uint32_t& r1, uint32_t& r2, uint32_t& r3) {
    asm volatile("ldmatrix.sync.aligned.m8n8.x4.trans.shared.b16 {%0,%1,%2,%3}, [%4];" : "=r"(r0), "=r"(r1), "=r"(r2), "=r"(r3) : "r"(a) : "memory");
}
__device__ __forceinline__ void mma16816(float* c, uint32_t a0, uint32_t a1, uint32_t a2, uint32_t a3, uint32_t b0, uint32_t b1) {
    asm volatile("mma.sync.aligned.m16n8k16.row.col.f32.bf16.bf16.f32 {%0,%1,%2,%3}, {%4,%5,%6,%7}, {%8,%9}, {%0,%1,%2,%3};"
                 : "+f"(c[0]), "+f"(c[1]), "+f"(c[2]), "+f"(c[3]) : "r"(a0), "r"(a1), "r"(a2), "r"(a3), "r"(b0), "r"(b1));
}
__device__ __forceinline__ void mma1688z(float* c, uint32_t a0, uint32_t a1, uint32_t b0) {
    asm volatile("mma.sync.aligned.m16n8k8.row.col.f32.bf16.bf16.f32 {%0,%1,%2,%3}, {%4,%5}, {%6}, {%7,%7,%7,%7};"
                 : "=f"(c[0]), "=f"(c[1]), "=f"(c[2]), "=f"(c[3]) : "r"(a0), "r"(a1), "r"(b0), "f"(0.f));
}
__device__ __forceinline__ uint32_t pack2(float lo, float hi) { uint32_t r; asm("cvt.rn.bf16x2.f32 %0, %1, %2;" : "=r"(r) : "f"(hi), "f"(lo)); return r; }
__device__ __forceinline__ uint32_t max2(uint32_t a, uint32_t b) { uint32_t r; asm("max.NaN.bf16x2 %0, %1, %2;" : "=r"(r) : "r"(a), "r"(b)); return r; }
__device__ __forceinline__ float bf_lo(uint32_t u) { return __uint_as_float(u << 16); }
__device__ __forceinline__ float bf_hi(uint32_t u) { return __uint_as_float(u & 0xffff0000u); }
__device__ __forceinline__ float ex2(float x) { float y; asm("ex2.approx.ftz.f32 %0, %1;" : "=f"(y) : "f"(x)); return y; }
__device__ __forceinline__ float rcpa(float x) { float y; asm("rcp.approx.ftz.f32 %0, %1;" : "=f"(y) : "f"(x)); return y; }
__device__ __forceinline__ uint32_t mapa(uint32_t a, int r) { uint32_t o; asm("mapa.shared::cluster.u32 %0, %1, %2;" : "=r"(o) : "r"(a), "r"(r)); return o; }
__device__ __forceinline__ bool elect_one() { uint32_t p; asm volatile("{\n.reg .pred P;\nelect.sync _|P, 0xffffffff;\nselp.u32 %0, 1, 0, P;\n}" : "=r"(p)); return p; }
__device__ __forceinline__ void st_async4(uint32_t a, uint32_t x, uint32_t y, uint32_t z, uint32_t w, uint32_t b) {
    asm volatile("st.async.weak.shared::cluster.mbarrier::complete_tx::bytes.v4.b32 [%0], {%1,%2,%3,%4}, [%5];" :: "r"(a), "r"(x), "r"(y), "r"(z), "r"(w), "r"(b) : "memory");
}
__device__ __forceinline__ void st_async2(uint32_t a, float x, float y, uint32_t b) {
    asm volatile("st.async.weak.shared::cluster.mbarrier::complete_tx::bytes.v2.f32 [%0], {%1,%2}, [%3];" :: "r"(a), "f"(x), "f"(y), "r"(b) : "memory");
}
__device__ __forceinline__ float2 lds2(uint32_t a) { float2 x; asm volatile("ld.shared.v2.f32 {%0,%1}, [%2];" : "=f"(x.x), "=f"(x.y) : "r"(a) : "memory"); return x; }
__device__ __forceinline__ void stg4(void* p, uint4 v) {
    asm volatile("st.global.L1::no_allocate.v4.u32 [%0], {%1,%2,%3,%4};" :: "l"(p), "r"(v.x), "r"(v.y), "r"(v.z), "r"(v.w) : "memory");
}
__device__ __forceinline__ uint4 shfl_xor4(uint4 v, int m) {
    return make_uint4(__shfl_xor_sync(~0u, v.x, m), __shfl_xor_sync(~0u, v.y, m), __shfl_xor_sync(~0u, v.z, m), __shfl_xor_sync(~0u, v.w, m));
}

__device__ __forceinline__ int kv_rows(int kvr, int i) {
    return kvr + ((i & 4) ? (i & 1) * 32 + (i & 2) * 64 : (i & 1) * 128 + (i & 2) * 16) + (i >> 3) * 2048;
}
__device__ __forceinline__ int q_rows(int qr, int i) { return (qr ^ ((i & 2) * 8)) + (i & 1) * 128 + (i >> 2) * 2048; }

__global__ void __launch_bounds__(NTHR, 2)
linformer_kernel(const __grid_constant__ Params pp,
                 const __grid_constant__ CUtensorMap mk, const __grid_constant__ CUtensorMap mv,
                 const __grid_constant__ CUtensorMap me, const __grid_constant__ CUtensorMap mf,
                 const __grid_constant__ CUtensorMap mq) {
    const unsigned b = blockIdx.x;
    const int tid = threadIdx.x, lane = tid & 31;
    asm volatile("prefetch.global.L2 [%0];"
                 :: "l"((tid < 256 ? pp.k + (b << 15) : ((b & 1) ? pp.f : pp.e) + ((b & 6) << 12) - 32768) + tid * 128) : "memory");
    if (tid == 288) {
        asm volatile("prefetch.tensormap [%0];" :: "l"(&me) : "memory");
        asm volatile("prefetch.tensormap [%0];" :: "l"(&mf) : "memory");
        asm volatile("prefetch.tensormap [%0];" :: "l"(&mk) : "memory");
    }
    const int grp = b >> 4, j = b & 15;
    const int dh = j & 1, ne = j >> 1;
    const int kvr = grp * 256 + (ne & 3) * 8 + (ne & 4) * 16;
    const int qr = grp * 256 + (j & 3) * 4 + (j & 4) * 12 + (j & 8) * 8;
    extern __shared__ __align__(1024) char smem_raw[];
    const uint32_t sbase = smem_u32(smem_raw);
    const uint32_t sproj = sbase + STAGES * UB, srecv = sproj + 8192, sfrag = srecv + 8192;
    const uint32_t bfull = sfrag + 16384, bempty = bfull + 8 * STAGES, bproj = bempty + 8 * STAGES, bred = bproj + 8, bfrag = bred + 64;
    const int warp = __shfl_sync(~0u, tid >> 5, 0);
    const bool el = elect_one();
    if (warp == 0) {
        unsigned tz; asm volatile("mov.u32 %0, %%globaltimer_lo;" : "=r"(tz));
        uint64_t pol;
        asm("createpolicy.fractional.L2::evict_first.b64 %0, 1.0;" : "=l"(pol));
        if (el) {
            #pragma unroll
            for (int p = 0; p < NPRE; p++) mbar_init(bfull + 8 * p, 1);
            mbar_init(bproj, 1);
            mbar_expect_tx(bproj, 8192);
            tma_load_proj(sproj, &me, (kvr & 255) * 8, bproj);
            tma_load_proj(sproj + 4096, &mf, (kvr & 255) * 8, bproj);
            #pragma unroll
            for (int p = 0; p < NPRE; p++) {
                mbar_expect_tx(bfull + 8 * p, UB);
                tma_load4(sbase + p * UB, &mk, dh, kv_rows(kvr, p), bfull + 8 * p, pol);
            }
            asm volatile("prefetch.tensormap [%0];" :: "l"(&mv) : "memory");
        }
        asm volatile("barrier.arrive 2, 128;" ::: "memory");
        if (el) asm volatile("prefetch.tensormap [%0];" :: "l"(&mq) : "memory");
        const bool last = grp == 7;
        const Pace pc = last ? pp.c[1] : pp.c[0];
        const int step = pc.step, tail0 = pc.tail0, tail1 = pc.tail1;
        unsigned long long m = QMASK >> NPRE;
        unsigned dl = tz + pc.off;
        int ik = NPRE, iq = 0;
        int s = NPRE, sv = NPRE - 4 - last;
        unsigned ph = 1, phv = 0;
        asm volatile("barrier.sync 1, %0;" :: "n"(NTHR) : "memory");
        asm volatile("barrier.cluster.arrive.relaxed.aligned;" ::: "memory");
        #pragma unroll 1
        for (int t = NPRE; t < NU; t++) {
            const bool isq = m & 1; m >>= 1;
            const CUtensorMap* mp = isq ? &mq : (ik & 4) ? &mv : &mk;
            const int c2 = isq ? 0 : dh;
            const int c3 = isq ? q_rows(qr, iq) : kv_rows(kvr, ik);
            int it = 0;
            unsigned now;
            while (true) {
                const uint32_t slot_free = mbar_test(bempty + 8 * s, ph);
                asm volatile("mov.u32 %0, %%globaltimer_lo;" : "=r"(now));
                if (slot_free && (int)(now - dl) >= 0) break;
                if (++it > (1 << 22)) __trap();
            }
            if (el) {
                mbar_expect_tx(bfull + 8 * s, UB);
                tma_load4(sbase + s * UB, mp, c2, c3, bfull + 8 * s, pol);
            }
            if (isq) iq++; else ik++;
            if ((int)(now - PACE_SLACK - dl) > 0) dl = now - PACE_SLACK;
            dl += t < 8 ? step : t >= LAST_KV + 2 ? tail1 : t >= LAST_KV ? tail0 : mbar_test(bfull + 8 * sv, phv) ? step - PACE_DN : step + PACE_UP;
            if (++s == STAGES) { s = 0; ph ^= 1; }
            if (++sv == STAGES) { sv = 0; phv ^= 1; }
        }
        asm volatile("barrier.cluster.wait.aligned;" ::: "memory");
        return;
    }
    if (warp <= 3) {
        asm volatile("barrier.sync 2, 128;" ::: "memory");
        if (el) {
            if (warp == 1) {
                #pragma unroll
                for (int i = 0; i < STAGES; i++) mbar_init(bempty + 8 * i, 4);
                #pragma unroll
                for (int i = NPRE; i < STAGES; i++) mbar_init(bfull + 8 * i, 1);
            } else {
                const uint32_t bx = warp == 2 ? bred : bfrag;
                #pragma unroll
                for (int i = 0; i < 8; i++) mbar_init(bx + 8 * i, 1);
                #pragma unroll
                for (int i = 0; i < 8; i++) mbar_expect_tx(bx + 8 * i, 2048);
                asm volatile("fence.mbarrier_init.release.cluster;" ::: "memory");
            }
        }
    }
    asm volatile("barrier.sync 1, %0;" :: "n"(NTHR) : "memory");
    asm volatile("barrier.cluster.arrive.relaxed.aligned;" ::: "memory");
    const int g = lane >> 2;
    const int mi = lane >> 3, li = lane & 7;
    if (warp == 5) {
        uint32_t rbase[4];
        #pragma unroll
        for (int rr = 0; rr < 4; rr++) rbase[rr] = mapa(sbase, (4 * rr + mi + j + 1) & 15) - sbase;
        const uint32_t la0 = sfrag + (dh * 8 + ne) * 128 + ((li ^ (2 * (ne & 3))) << 4);
        asm volatile("barrier.cluster.wait.aligned;" ::: "memory");
        #pragma unroll 1
        for (int px = 0; px < 8; px++) {
            const uint32_t ad = srecv + (px & 3) * 2048 + lane * 8;
            mbar_wait_cluster(bred + px * 8);
            float2 x[8];
            #pragma unroll
            for (int i = 0; i < 8; i++) x[i] = lds2(ad + i * 256);
            const uint32_t o = pack2(((x[0].x + x[1].x) + (x[2].x + x[3].x)) + ((x[4].x + x[5].x) + (x[6].x + x[7].x)),
                                     ((x[0].y + x[1].y) + (x[2].y + x[3].y)) + ((x[4].y + x[5].y) + (x[6].y + x[7].y)));
            const uint32_t w0 = __shfl_sync(~0u, o, 4 * li), w1 = __shfl_sync(~0u, o, 4 * li + 1);
            const uint32_t w2 = __shfl_sync(~0u, o, 4 * li + 2), w3 = __shfl_sync(~0u, o, 4 * li + 3);
            #pragma unroll
            for (int rr = 0; rr < 4; rr++) st_async4(la0 + px * 2048 + rbase[rr], w0, w1, w2, w3, bfrag + px * 8 + rbase[rr]);
        }
        return;
    }
    const int w = (warp - 1 - (warp > 5)) & 3;
    int n0 = w >> 1, n1 = 14;
    if (warp < 5) {
        const uint32_t r0 = mapa(sbase, 4 * w + dh) - sbase, r1 = mapa(sbase, 4 * w + 2 + dh) - sbase;
        const uint32_t ra = srecv + ne * 256 + lane * 8;
        const uint32_t aoff = sbase + ((mi >> 1) * 8 + li) * 128 + (((2 * w + (mi & 1)) ^ li) << 4);
        const uint32_t boff = sproj + li * 128 + ((mi ^ li) << 4);
        unsigned long long m = ~QMASK, gm = QMASK << STAGES;
        int s = 0; unsigned par = 0;
        asm volatile("barrier.cluster.wait.aligned;" ::: "memory");
        mbar_wait(bproj, 0);
        #pragma unroll 1
        for (int px = 0; px < 8; px++) {
            float acc[2][4] = {};
            #pragma unroll 1
            for (int i = (px & 1) * 4; i < (px & 1) * 4 + 4; i++) {
                uint32_t bb[8];
                ldsm4(boff + i * 1024, bb[0], bb[1], bb[2], bb[3]);
                ldsm4((boff ^ 64) + i * 1024, bb[4], bb[5], bb[6], bb[7]);
                if (gm & 1) mbar_wait(bempty + 8 * s, par ^ 1);
                mbar_wait(bfull + 8 * s, par);
                uint32_t a[4][4];
                #pragma unroll
                for (int ks = 0; ks < 4; ks++) ldsm4t(aoff + s * UB + ks * 2048, a[ks][0], a[ks][1], a[ks][2], a[ks][3]);
                #pragma unroll
                for (int ks = 0; ks < 4; ks++) mma16816(acc[ks & 1], a[ks][0], a[ks][1], a[ks][2], a[ks][3], bb[2 * ks], bb[2 * ks + 1]);
                if ((i & 3) == 3) {
                    st_async2(ra + (px & 3) * 2048 + r0, acc[0][0] + acc[1][0], acc[0][1] + acc[1][1], bred + px * 8 + r0);
                    st_async2(ra + (px & 3) * 2048 + r1, acc[0][2] + acc[1][2], acc[0][3] + acc[1][3], bred + px * 8 + r1);
                }
                __syncwarp();
                if (lane == 0) mbar_arrive(bempty + 8 * s);
                const int dt = __ffs((unsigned)(m >> 1));
                m >>= dt; gm >>= dt; s += dt;
                if (s >= STAGES) { s -= STAGES; par ^= 1; }
            }
        }
        n0 += 14; n1 = 16;
    } else {
        asm volatile("barrier.cluster.wait.aligned;" ::: "memory");
    }
    const int rg = w & 1;
    const int lr = (li & 4) | ((li & 1) << 1) | ((li >> 1) & 1);
    const uint32_t qoff = sbase + (rg * 2 + (mi & 1)) * 2048 + lr * 128;
    const uint32_t qx = (mi >> 1) ^ lr;
    bf16* obase = pp.out + (rg * 16 + ((g & 4) | ((g >> 1) & 1))) * DH + li * 8;
    uint32_t kp[16], vp[16];
    unsigned long long m = warp < 5 ? 3ull << (NU - 2) : QMASK;
    if (w & 2) m &= m - 1;
    #pragma unroll 1
    for (int n = n0; n < n1; n += 2) {
        const int t = __ffsll(m) - 1; m &= m - 1; m &= m - 1;
        const int r = (t * 26) >> 8, s = t - r * STAGES;
        const unsigned par = r & 1;
        const int hg = n >> 2;
        bf16* orow = obase + (size_t)q_rows(qr, n) * 8 * DH;
        const bool first = (n & 2) == 0 || n == n0;
        if (first) {
            mbar_wait_cluster(bfrag + 16 * hg);
            #pragma unroll
            for (int i = 0; i < 4; i++)
                ldsm4t(sfrag + hg * 4096 + i * 512 + mi * 128 + ((li ^ (2 * mi)) << 4), kp[4 * i], kp[4 * i + 1], kp[4 * i + 2], kp[4 * i + 3]);
        }
        if (t >= STAGES) mbar_wait(bempty + 8 * s, par ^ 1);
        mbar_wait(bfull + 8 * s, par);
        uint32_t a[8][4];
        #pragma unroll
        for (int ks = 0; ks < 8; ks++) ldsm4(qoff + s * UB + (ks >> 2) * 1024 + ((qx ^ ((ks & 3) << 1)) << 4), a[ks][0], a[ks][1], a[ks][2], a[ks][3]);
        float sc[4][4] = {};
        #pragma unroll
        for (int ks = 0; ks < 8; ks++) mma16816(sc[ks & 3], a[ks][0], a[ks][1], a[ks][2], a[ks][3], kp[2 * ks], kp[2 * ks + 1]);
        __syncwarp();
        if (lane < 2) mbar_arrive(bempty + 8 * s);
        const float scale = 0.08838834764831845f, l2e = 1.4426950408889634f;
        uint32_t u0 = pack2((sc[0][0] + sc[1][0]) + (sc[2][0] + sc[3][0]), (sc[0][2] + sc[1][2]) + (sc[2][2] + sc[3][2]));
        uint32_t u1 = pack2((sc[0][1] + sc[1][1]) + (sc[2][1] + sc[3][1]), (sc[0][3] + sc[1][3]) + (sc[2][3] + sc[3][3]));
        u0 = pack2(bf_lo(u0) * scale, bf_hi(u0) * scale);
        u1 = pack2(bf_lo(u1) * scale, bf_hi(u1) * scale);
        uint32_t mx = max2(u0, u1);
        {
            const uint32_t a1 = __shfl_xor_sync(~0u, mx, 1), a2 = __shfl_xor_sync(~0u, mx, 2), a3 = __shfl_xor_sync(~0u, mx, 3);
            mx = max2(max2(mx, a1), max2(a2, a3));
        }
        const float e0 = ex2((bf_lo(u0) - bf_lo(mx)) * l2e), e1 = ex2((bf_lo(u1) - bf_lo(mx)) * l2e);
        const float e2 = ex2((bf_hi(u0) - bf_hi(mx)) * l2e), e3 = ex2((bf_hi(u1) - bf_hi(mx)) * l2e);
        float s0 = e0 + e1, s1 = e2 + e3;
        {
            const float a1 = __shfl_xor_sync(~0u, s0, 1), b1 = __shfl_xor_sync(~0u, s1, 1);
            const float a2 = __shfl_xor_sync(~0u, s0, 2), b2 = __shfl_xor_sync(~0u, s1, 2);
            const float a3 = __shfl_xor_sync(~0u, s0, 3), b3 = __shfl_xor_sync(~0u, s1, 3);
            s0 = (s0 + a1) + (a2 + a3); s1 = (s1 + b1) + (b2 + b3);
        }
        const float r0 = rcpa(s0), r1 = rcpa(s1);
        const uint32_t pa0 = pack2(e0 * r0, e1 * r0), pa1 = pack2(e2 * r1, e3 * r1);
        if (first) {
            mbar_wait_cluster(bfrag + 16 * hg + 8);
            #pragma unroll
            for (int i = 0; i < 4; i++)
                ldsm4(sfrag + hg * 4096 + 2048 + i * 512 + (li >> 1) * 128 + (((2 * mi + (li & 1)) ^ (li & 6)) << 4), vp[4 * i], vp[4 * i + 1], vp[4 * i + 2], vp[4 * i + 3]);
        }
        #pragma unroll
        for (int H = 0; H < 2; H++) {
            uint4 lo[2], hi[2];
            #pragma unroll
            for (int J = 0; J < 2; J++) {
                float c[4][4];
                #pragma unroll
                for (int u = 0; u < 4; u++) mma1688z(c[u], pa0, pa1, vp[H * 8 + J * 4 + u]);
                lo[J] = make_uint4(pack2(c[0][0], c[0][1]), pack2(c[1][0], c[1][1]), pack2(c[2][0], c[2][1]), pack2(c[3][0], c[3][1]));
                hi[J] = make_uint4(pack2(c[0][2], c[0][3]), pack2(c[1][2], c[1][3]), pack2(c[2][2], c[2][3]), pack2(c[3][2], c[3][3]));
            }
            const bool od = g & 1;
            const uint4 xl = shfl_xor4(od ? lo[0] : lo[1], 4), xh = shfl_xor4(od ? hi[0] : hi[1], 4);
            bf16* pe = orow + H * 64;
            stg4(pe, od ? xl : lo[0]);
            stg4(pe + 2 * DH, od ? lo[1] : xl);
            stg4(pe + 8 * DH, od ? xh : hi[0]);
            stg4(pe + 10 * DH, od ? hi[1] : xh);
        }
    }
}

typedef CUresult (*EncodeFn)(CUtensorMap*, CUtensorMapDataType, cuuint32_t, void*, const cuuint64_t*, const cuuint64_t*,
                             const cuuint32_t*, const cuuint32_t*, CUtensorMapInterleave, CUtensorMapSwizzle,
                             CUtensorMapL2promotion, CUtensorMapFloatOOBfill);

void make_map(EncodeFn enc, CUtensorMap* m, void* p, int d0, int row_bytes, int stride2, int d3, int stride3, int b2, int b3) {
    cuuint32_t es[4] = {1, 1, 1, 1};
    cuuint64_t d[4] = {(cuuint64_t)d0, 8, 2, (cuuint64_t)d3};
    cuuint64_t s[3] = {(cuuint64_t)row_bytes, (cuuint64_t)stride2, (cuuint64_t)stride3};
    cuuint32_t b[4] = {64, 8, (cuuint32_t)b2, (cuuint32_t)b3};
    enc(m, CU_TENSOR_MAP_DATA_TYPE_BFLOAT16, 4, p, d, s, b, es, CU_TENSOR_MAP_INTERLEAVE_NONE, CU_TENSOR_MAP_SWIZZLE_128B,
        CU_TENSOR_MAP_L2_PROMOTION_L2_128B, CU_TENSOR_MAP_FLOAT_OOB_FILL_NONE);
}

void launch(void* const* d_in, void* d_out, const Pace& s0, const Pace& s1) {
    void* fn = nullptr;
    cudaDriverEntryPointQueryResult qr;
    cudaGetDriverEntryPoint("cuTensorMapEncodeTiled", &fn, cudaEnableDefault, &qr);
    EncodeFn enc = (EncodeFn)fn;
    CUtensorMap mq, mk, mv, me, mf;
    make_map(enc, &mq, d_in[0], 64, 256, 128, 8192, 2048, 2, 4);
    make_map(enc, &mk, d_in[1], 64, 256, 128, 8192, 2048, 1, 8);
    make_map(enc, &mv, d_in[2], 64, 256, 128, 8192, 2048, 1, 8);
    make_map(enc, &me, d_in[3], 768, 4096, 2048, 2, 512, 2, 2);
    make_map(enc, &mf, d_in[4], 768, 4096, 512, 2, 2048, 2, 2);
    Params pp;
    pp.k = (const char*)d_in[1];
    pp.e = (const char*)d_in[3];
    pp.f = (const char*)d_in[4];
    pp.out = (bf16*)d_out;
    pp.c[0] = s0; pp.c[1] = s1;
    cudaFuncSetAttribute(linformer_kernel, cudaFuncAttributeMaxDynamicSharedMemorySize, SMEM_BYTES);
    cudaFuncSetAttribute(linformer_kernel, cudaFuncAttributeNonPortableClusterSizeAllowed, 1);
    cudaLaunchConfig_t cfg = {};
    cfg.gridDim = dim3(128);
    cfg.blockDim = dim3(NTHR);
    cfg.dynamicSmemBytes = SMEM_BYTES;
    cfg.stream = cudaStreamPerThread;
    cudaLaunchAttribute at[2];
    at[0].id = cudaLaunchAttributeClusterDimension;
    at[0].val.clusterDim.x = 16; at[0].val.clusterDim.y = 1; at[0].val.clusterDim.z = 1;
    at[1].id = cudaLaunchAttributeClusterSchedulingPolicyPreference;
    at[1].val.clusterSchedulingPolicyPreference = cudaClusterSchedulingPolicyLoadBalancing;
    cfg.attrs = at; cfg.numAttrs = 2;
    cudaLaunchKernelEx(&cfg, linformer_kernel, pp, mk, mv, me, mf, mq);
}

}

extern "C" void kernel_launch(void* const* d_in, const int* in_sizes, int n_in, void* d_out, int out_size) {
    (void)in_sizes; (void)n_in; (void)out_size;
    lf::launch(d_in, d_out, {700, 329, 380, 345}, {860, 303, 360, 400});
}
```

```cpp
#include <cuda_runtime.h>
#include <cuda_bf16.h>
#include <cuda.h>
#include <stdint.h>

namespace lf {

typedef __nv_bfloat16 bf16;

constexpr int DH = 128;
constexpr int NU = 48;
constexpr int UB = 8192;
constexpr int STAGES = 10;
constexpr int NTHR = 320;
constexpr int NPRE = 4;
constexpr int SMEM_BYTES = STAGES * UB + 8192 + 8192 + 16384 + 1024;

constexpr char ORDER[NU + 1] = "KKKKKKKKQKKQKKQKQKKKQKKQKKQKQKKKQKQKKQKQKKKKQQQQ";
constexpr int LAST_KV = 43;
constexpr int unit_pos(char kind, int idx) {
    for (int t = 0; t < NU; t++) if (ORDER[t] == kind && idx-- == 0) return t;
    return -1;
}
constexpr unsigned long long q_mask() {
    unsigned long long m = 0;
    for (int t = 0; t < NU; t++) if (ORDER[t] == 'Q') m |= 1ull << t;
    return m;
}
constexpr bool order_ok() {
    if (unit_pos('K', 31) != LAST_KV || unit_pos('Q', 14) != NU - 2 || unit_pos('Q', 15) != NU - 1 || unit_pos('K', NPRE) != NPRE) return false;
    for (int i = 0; i < 16; i++) {
        if (unit_pos('Q', i) < unit_pos('K', i / 4 * 8 + 7)) return false;
        if (unit_pos('Q', i) - (i < 2 ? unit_pos('K', 3) : i < 14 ? unit_pos('Q', i - 2) : LAST_KV) > STAGES) return false;
    }
    for (int i = 1; i < 32; i++) if (unit_pos('K', i) - unit_pos('K', i - 1) > STAGES) return false;
    for (int h = 0; h < 2; h++)
        if (unit_pos('Q', 4 * h) + STAGES > unit_pos('K', 8 * h + 19) || unit_pos('Q', 4 * h + 2) + STAGES > unit_pos('K', 8 * h + 23)) return false;
    return true;
}
static_assert(order_ok(), "invalid unit order");
constexpr unsigned long long QMASK = q_mask();

constexpr int PACE_UP = 18, PACE_DN = 11, PACE_SLACK = 200;
struct Pace { unsigned short off, step, tail0, tail1; };
struct Params {
    const char* k;
    const char* e;
    const char* f;
    bf16* out;
    Pace c[2];
};

__device__ __forceinline__ uint32_t smem_u32(const void* p) { return (uint32_t)__cvta_generic_to_shared(p); }
__device__ __forceinline__ void mbar_init(uint32_t bar, uint32_t cnt) { asm volatile("mbarrier.init.shared::cta.b64 [%0], %1;" :: "r"(bar), "r"(cnt) : "memory"); }
__device__ __forceinline__ void mbar_expect_tx(uint32_t bar, uint32_t bytes) { asm volatile("mbarrier.arrive.expect_tx.shared::cta.b64 _, [%0], %1;" :: "r"(bar), "r"(bytes) : "memory"); }
__device__ __forceinline__ void mbar_arrive(uint32_t bar) { asm volatile("mbarrier.arrive.shared::cta.b64 _, [%0];" :: "r"(bar) : "memory"); }
__device__ __forceinline__ void mbar_wait(uint32_t bar, uint32_t parity) {
    uint32_t done; int it = 0;
    do {
        asm volatile("{\n.reg .pred p;\nmbarrier.try_wait.parity.shared::cta.b64 p, [%1], %2;\nselp.u32 %0, 1, 0, p;\n}" : "=r"(done) : "r"(bar), "r"(parity) : "memory");
        if (++it > (1 << 22)) __trap();
    } while (!done);
}
__device__ __forceinline__ void mbar_wait_cluster(uint32_t bar) {
    uint32_t done; int it = 0;
    do {
        asm volatile("{\n.reg .pred p;\nmbarrier.try_wait.parity.acquire.cluster.shared::cta.b64 p, [%1], 0;\nselp.u32 %0, 1, 0, p;\n}" : "=r"(done) : "r"(bar) : "memory");
        if (++it > (1 << 22)) __trap();
    } while (!done);
}
__device__ __forceinline__ uint32_t mbar_test(uint32_t bar, uint32_t par) {
    uint32_t d;
    asm volatile("{\n.reg .pred p;\nmbarrier.test_wait.parity.shared::cta.b64 p, [%1], %2;\nselp.u32 %0, 1, 0, p;\n}" : "=r"(d) : "r"(bar), "r"(par) : "memory");
    return d;
}
__device__ __forceinline__ void tma_load4(uint32_t dst, const CUtensorMap* m, int c2, int c3, uint32_t bar, uint64_t pol) {
    asm volatile("cp.async.bulk.tensor.4d.shared::cluster.global.mbarrier::complete_tx::bytes.L2::cache_hint [%0], [%1, {%3, %3, %4, %5}], [%2], %6;"
                 :: "r"(dst), "l"(m), "r"(bar), "r"(0), "r"(c2), "r"(c3), "l"(pol) : "memory");
}
__device__ __forceinline__ void tma_load_proj(uint32_t dst, const CUtensorMap* m, int c0, uint32_t bar) {
    asm volatile("cp.async.bulk.tensor.4d.shared::cluster.global.mbarrier::complete_tx::bytes [%0], [%1, {%4, %3, %3, %3}], [%2];"
                 :: "r"(dst), "l"(m), "r"(bar), "r"(0), "r"(c0) : "memory");
}
__device__ __forceinline__ void ldsm4(uint32_t a, uint32_t& r0, uint32_t& r1, uint32_t& r2, uint32_t& r3) {
    asm volatile("ldmatrix.sync.aligned.m8n8.x4.shared.b16 {%0,%1,%2,%3}, [%4];" : "=r"(r0), "=r"(r1), "=r"(r2), "=r"(r3) : "r"(a) : "memory");
}
__device__ __forceinline__ void ldsm4t(uint32_t a, uint32_t& r0, uint32_t& r1, uint32_t& r2, uint32_t& r3) {
    asm volatile("ldmatrix.sync.aligned.m8n8.x4.trans.shared.b16 {%0,%1,%2,%3}, [%4];" : "=r"(r0), "=r"(r1), "=r"(r2), "=r"(r3) : "r"(a) : "memory");
}
__device__ __forceinline__ void mma16816(float* c, uint32_t a0, uint32_t a1, uint32_t a2, uint32_t a3, uint32_t b0, uint32_t b1) {
    asm volatile("mma.sync.aligned.m16n8k16.row.col.f32.bf16.bf16.f32 {%0,%1,%2,%3}, {%4,%5,%6,%7}, {%8,%9}, {%0,%1,%2,%3};"
                 : "+f"(c[0]), "+f"(c[1]), "+f"(c[2]), "+f"(c[3]) : "r"(a0), "r"(a1), "r"(a2), "r"(a3), "r"(b0), "r"(b1));
}
__device__ __forceinline__ void mma1688z(float* c, uint32_t a0, uint32_t a1, uint32_t b0) {
    asm volatile("mma.sync.aligned.m16n8k8.row.col.f32.bf16.bf16.f32 {%0,%1,%2,%3}, {%4,%5}, {%6}, {%7,%7,%7,%7};"
                 : "=f"(c[0]), "=f"(c[1]), "=f"(c[2]), "=f"(c[3]) : "r"(a0), "r"(a1), "r"(b0), "f"(0.f));
}
__device__ __forceinline__ uint32_t pack2(float lo, float hi) { uint32_t r; asm("cvt.rn.bf16x2.f32 %0, %1, %2;" : "=r"(r) : "f"(hi), "f"(lo)); return r; }
__device__ __forceinline__ uint32_t max2(uint32_t a, uint32_t b) { uint32_t r; asm("max.NaN.bf16x2 %0, %1, %2;" : "=r"(r) : "r"(a), "r"(b)); return r; }
__device__ __forceinline__ float bf_lo(uint32_t u) { return __uint_as_float(u << 16); }
__device__ __forceinline__ float bf_hi(uint32_t u) { return __uint_as_float(u & 0xffff0000u); }
__device__ __forceinline__ float ex2(float x) { float y; asm("ex2.approx.ftz.f32 %0, %1;" : "=f"(y) : "f"(x)); return y; }
__device__ __forceinline__ float rcpa(float x) { float y; asm("rcp.approx.ftz.f32 %0, %1;" : "=f"(y) : "f"(x)); return y; }
__device__ __forceinline__ uint32_t mapa(uint32_t a, int r) { uint32_t o; asm("mapa.shared::cluster.u32 %0, %1, %2;" : "=r"(o) : "r"(a), "r"(r)); return o; }
__device__ __forceinline__ bool elect_one() { uint32_t p; asm volatile("{\n.reg .pred P;\nelect.sync _|P, 0xffffffff;\nselp.u32 %0, 1, 0, P;\n}" : "=r"(p)); return p; }
__device__ __forceinline__ void st_async4(uint32_t a, uint32_t x, uint32_t y, uint32_t z, uint32_t w, uint32_t b) {
    asm volatile("st.async.weak.shared::cluster.mbarrier::complete_tx::bytes.v4.b32 [%0], {%1,%2,%3,%4}, [%5];" :: "r"(a), "r"(x), "r"(y), "r"(z), "r"(w), "r"(b) : "memory");
}
__device__ __forceinline__ void st_async2(uint32_t a, float x, float y, uint32_t b) {
    asm volatile("st.async.weak.shared::cluster.mbarrier::complete_tx::bytes.v2.f32 [%0], {%1,%2}, [%3];" :: "r"(a), "f"(x), "f"(y), "r"(b) : "memory");
}
__device__ __forceinline__ float2 lds2(uint32_t a) { float2 x; asm volatile("ld.shared.v2.f32 {%0,%1}, [%2];" : "=f"(x.x), "=f"(x.y) : "r"(a) : "memory"); return x; }
__device__ __forceinline__ void stg4(void* p, uint4 v) {
    asm volatile("st.global.L1::no_allocate.v4.u32 [%0], {%1,%2,%3,%4};" :: "l"(p), "r"(v.x), "r"(v.y), "r"(v.z), "r"(v.w) : "memory");
}
__device__ __forceinline__ uint4 shfl_xor4(uint4 v, int m) {
    return make_uint4(__shfl_xor_sync(~0u, v.x, m), __shfl_xor_sync(~0u, v.y, m), __shfl_xor_sync(~0u, v.z, m), __shfl_xor_sync(~0u, v.w, m));
}

__device__ __forceinline__ int kv_rows(int kvr, int i) {
    return kvr + ((i & 4) ? (i & 1) * 32 + (i & 2) * 64 : (i & 1) * 128 + (i & 2) * 16) + (i >> 3) * 2048;
}
__device__ __forceinline__ int q_rows(int qr, int i) { return (qr ^ ((i & 2) * 8) ^ ((i & 1) * 128)) + (i >> 2) * 2048; }

__global__ void __launch_bounds__(NTHR, 2)
linformer_kernel(const __grid_constant__ Params pp,
                 const __grid_constant__ CUtensorMap mk, const __grid_constant__ CUtensorMap mv,
                 const __grid_constant__ CUtensorMap me, const __grid_constant__ CUtensorMap mf,
                 const __grid_constant__ CUtensorMap mq) {
    const unsigned b = blockIdx.x;
    const int tid = threadIdx.x, lane = tid & 31;
    asm volatile("prefetch.global.L2 [%0];"
                 :: "l"((tid < 256 ? pp.k + (b << 15) : ((b & 1) ? pp.f : pp.e) + ((b & 6) << 12) - 32768) + tid * 128) : "memory");
    if (tid == 288) {
        asm volatile("prefetch.tensormap [%0];" :: "l"(&me) : "memory");
        asm volatile("prefetch.tensormap [%0];" :: "l"(&mf) : "memory");
        asm volatile("prefetch.tensormap [%0];" :: "l"(&mk) : "memory");
    }
    const int grp = b >> 4, j = b & 15;
    const int dh = j & 1, ne = j >> 1;
    const int kvr = grp * 256 + (ne & 3) * 8 + (ne & 4) * 16;
    const int qr = grp * 256 + 144 + (j & 7) * 4 + (j & 8) * 8;
    extern __shared__ __align__(1024) char smem_raw[];
    const uint32_t sbase = smem_u32(smem_raw);
    const uint32_t sproj = sbase + STAGES * UB, srecv = sproj + 8192, sfrag = srecv + 8192;
    const uint32_t bfull = sfrag + 16384, bempty = bfull + 8 * STAGES, bproj = bempty + 8 * STAGES, bred = bproj + 8, bfrag = bred + 64;
    const int warp = __shfl_sync(~0u, tid >> 5, 0);
    const bool el = elect_one();
    if (warp == 0) {
        unsigned tz; asm volatile("mov.u32 %0, %%globaltimer_lo;" : "=r"(tz));
        uint64_t pol;
        asm("createpolicy.fractional.L2::evict_first.b64 %0, 1.0;" : "=l"(pol));
        if (el) {
            #pragma unroll
            for (int p = 0; p < NPRE; p++) mbar_init(bfull + 8 * p, 1);
            mbar_init(bproj, 1);
            mbar_expect_tx(bproj, 8192);
            tma_load_proj(sproj, &me, (kvr & 255) * 8, bproj);
            tma_load_proj(sproj + 4096, &mf, (kvr & 255) * 8, bproj);
            #pragma unroll
            for (int p = 0; p < NPRE; p++) {
                mbar_expect_tx(bfull + 8 * p, UB);
                tma_load4(sbase + p * UB, &mk, dh, kv_rows(kvr, p), bfull + 8 * p, pol);
            }
            asm volatile("prefetch.tensormap [%0];" :: "l"(&mv) : "memory");
        }
        asm volatile("barrier.arrive 2, 128;" ::: "memory");
        if (el) asm volatile("prefetch.tensormap [%0];" :: "l"(&mq) : "memory");
        const bool last = grp == 7;
        const Pace pc = last ? pp.c[1] : pp.c[0];
        const int step = pc.step, tail0 = pc.tail0, tail1 = pc.tail1;
        unsigned long long m = QMASK >> NPRE;
        unsigned dl = tz + pc.off;
        int ik = NPRE, iq = 0;
        int s = NPRE, sv = NPRE - 4 - last;
        unsigned ph = 1, phv = 0;
        asm volatile("barrier.sync 1, %0;" :: "n"(NTHR) : "memory");
        asm volatile("barrier.cluster.arrive.relaxed.aligned;" ::: "memory");
        #pragma unroll 1
        for (int t = NPRE; t < NU; t++) {
            const bool isq = m & 1; m >>= 1;
            const CUtensorMap* mp = isq ? &mq : (ik & 4) ? &mv : &mk;
            const int c2 = isq ? 0 : dh;
            const int c3 = isq ? q_rows(qr, iq) : kv_rows(kvr, ik);
            int it = 0;
            unsigned now;
            while (true) {
                const uint32_t slot_free = mbar_test(bempty + 8 * s, ph);
                asm volatile("mov.u32 %0, %%globaltimer_lo;" : "=r"(now));
                if (slot_free && (int)(now - dl) >= 0) break;
                if (++it > 4096) { dl = now; if (it > (1 << 22)) __trap(); }
            }
            if (el) {
                mbar_expect_tx(bfull + 8 * s, UB);
                tma_load4(sbase + s * UB, mp, c2, c3, bfull + 8 * s, pol);
            }
            if (isq) iq++; else ik++;
            if ((int)(now - PACE_SLACK - dl) > 0) dl = now - PACE_SLACK;
            dl += t < 8 ? step : t >= LAST_KV + 2 ? tail1 : t >= LAST_KV ? tail0 : mbar_test(bfull + 8 * sv, phv) ? step - PACE_DN : step + PACE_UP;
            if (++s == STAGES) { s = 0; ph ^= 1; }
            if (++sv == STAGES) { sv = 0; phv ^= 1; }
        }
        asm volatile("barrier.cluster.wait.aligned;" ::: "memory");
        return;
    }
    if (warp <= 3) {
        asm volatile("barrier.sync 2, 128;" ::: "memory");
        if (el) {
            if (warp == 1) {
                #pragma unroll
                for (int i = 0; i < STAGES; i++) mbar_init(bempty + 8 * i, 4);
                #pragma unroll
                for (int i = NPRE; i < STAGES; i++) mbar_init(bfull + 8 * i, 1);
            } else {
                const uint32_t bx = warp == 2 ? bred : bfrag;
                #pragma unroll
                for (int i = 0; i < 8; i++) mbar_init(bx + 8 * i, 1);
                #pragma unroll
                for (int i = 0; i < 8; i++) mbar_expect_tx(bx + 8 * i, 2048);
                asm volatile("fence.mbarrier_init.release.cluster;" ::: "memory");
            }
        }
    }
    asm volatile("barrier.sync 1, %0;" :: "n"(NTHR) : "memory");
    asm volatile("barrier.cluster.arrive.relaxed.aligned;" ::: "memory");
    const int g = lane >> 2;
    const int mi = lane >> 3, li = lane & 7;
    if (warp == 5) {
        uint32_t rbase[4];
        #pragma unroll
        for (int rr = 0; rr < 4; rr++) rbase[rr] = mapa(sbase, (4 * rr + mi + j + 1) & 15) - sbase;
        const uint32_t la0 = sfrag + (dh * 8 + ne) * 128 + ((li ^ (2 * (ne & 3))) << 4);
        asm volatile("barrier.cluster.wait.aligned;" ::: "memory");
        #pragma unroll 1
        for (int px = 0; px < 8; px++) {
            const uint32_t ad = srecv + (px & 3) * 2048 + lane * 8;
            mbar_wait_cluster(bred + px * 8);
            float2 x[8];
            #pragma unroll
            for (int i = 0; i < 8; i++) x[i] = lds2(ad + i * 256);
            const uint32_t o = pack2(((x[0].x + x[1].x) + (x[2].x + x[3].x)) + ((x[4].x + x[5].x) + (x[6].x + x[7].x)),
                                     ((x[0].y + x[1].y) + (x[2].y + x[3].y)) + ((x[4].y + x[5].y) + (x[6].y + x[7].y)));
            const uint32_t w0 = __shfl_sync(~0u, o, 4 * li), w1 = __shfl_sync(~0u, o, 4 * li + 1);
            const uint32_t w2 = __shfl_sync(~0u, o, 4 * li + 2), w3 = __shfl_sync(~0u, o, 4 * li + 3);
            #pragma unroll
            for (int rr = 0; rr < 4; rr++) st_async4(la0 + px * 2048 + rbase[rr], w0, w1, w2, w3, bfrag + px * 8 + rbase[rr]);
        }
        return;
    }
    const int w = (warp - 1 - (warp > 5)) & 3;
    int n0 = w >> 1, n1 = 14;
    if (warp < 5) {
        const uint32_t r0 = mapa(sbase, 4 * w + dh) - sbase, r1 = mapa(sbase, 4 * w + 2 + dh) - sbase;
        const uint32_t ra = srecv + ne * 256 + lane * 8;
        const uint32_t aoff = sbase + ((mi >> 1) * 8 + li) * 128 + (((2 * w + (mi & 1)) ^ li) << 4);
        const uint32_t boff = sproj + li * 128 + ((mi ^ li) << 4);
        unsigned long long m = ~QMASK, gm = QMASK << STAGES;
        int s = 0; unsigned par = 0;
        asm volatile("barrier.cluster.wait.aligned;" ::: "memory");
        mbar_wait(bproj, 0);
        #pragma unroll 1
        for (int px = 0; px < 8; px++) {
            float acc[2][4] = {};
            #pragma unroll 1
            for (int i = (px & 1) * 4; i < (px & 1) * 4 + 4; i++) {
                uint32_t bb[8];
                ldsm4(boff + i * 1024, bb[0], bb[1], bb[2], bb[3]);
                ldsm4((boff ^ 64) + i * 1024, bb[4], bb[5], bb[6], bb[7]);
                if (gm & 1) mbar_wait(bempty + 8 * s, par ^ 1);
                mbar_wait(bfull + 8 * s, par);
                uint32_t a[4][4];
                #pragma unroll
                for (int ks = 0; ks < 4; ks++) ldsm4t(aoff + s * UB + ks * 2048, a[ks][0], a[ks][1], a[ks][2], a[ks][3]);
                #pragma unroll
                for (int ks = 0; ks < 4; ks++) mma16816(acc[ks & 1], a[ks][0], a[ks][1], a[ks][2], a[ks][3], bb[2 * ks], bb[2 * ks + 1]);
                if ((i & 3) == 3) {
                    st_async2(ra + (px & 3) * 2048 + r0, acc[0][0] + acc[1][0], acc[0][1] + acc[1][1], bred + px * 8 + r0);
                    st_async2(ra + (px & 3) * 2048 + r1, acc[0][2] + acc[1][2], acc[0][3] + acc[1][3], bred + px * 8 + r1);
                }
                __syncwarp();
                if (lane == 0) mbar_arrive(bempty + 8 * s);
                const int dt = __ffs((unsigned)(m >> 1));
                m >>= dt; gm >>= dt; s += dt;
                if (s >= STAGES) { s -= STAGES; par ^= 1; }
            }
        }
        n0 += 14; n1 = 16;
    } else {
        asm volatile("barrier.cluster.wait.aligned;" ::: "memory");
    }
    const int rg = w & 1;
    const int lr = (li & 4) | ((li & 1) << 1) | ((li >> 1) & 1);
    const uint32_t qoff = sbase + (rg * 2 + (mi & 1)) * 2048 + lr * 128;
    const uint32_t qx = (mi >> 1) ^ lr;
    bf16* obase = pp.out + (rg * 16 + ((g & 4) | ((g >> 1) & 1))) * DH + li * 8;
    uint32_t kp[16], vp[16];
    unsigned long long m = warp < 5 ? 3ull << (NU - 2) : QMASK;
    if (w & 2) m &= m - 1;
    #pragma unroll 1
    for (int n = n0; n < n1; n += 2) {
        const int t = __ffsll(m) - 1; m &= m - 1; m &= m - 1;
        const int r = (t * 26) >> 8, s = t - r * STAGES;
        const unsigned par = r & 1;
        const int hg = n >> 2;
        bf16* orow = obase + (size_t)q_rows(qr, n) * 8 * DH;
        const bool first = (n & 2) == 0 || n == n0;
        if (first) {
            mbar_wait_cluster(bfrag + 16 * hg);
            #pragma unroll
            for (int i = 0; i < 4; i++)
                ldsm4t(sfrag + hg * 4096 + i * 512 + mi * 128 + ((li ^ (2 * mi)) << 4), kp[4 * i], kp[4 * i + 1], kp[4 * i + 2], kp[4 * i + 3]);
        }
        if (t >= STAGES) mbar_wait(bempty + 8 * s, par ^ 1);
        mbar_wait(bfull + 8 * s, par);
        uint32_t a[8][4];
        #pragma unroll
        for (int ks = 0; ks < 8; ks++) ldsm4(qoff + s * UB + (ks >> 2) * 1024 + ((qx ^ ((ks & 3) << 1)) << 4), a[ks][0], a[ks][1], a[ks][2], a[ks][3]);
        float sc[4][4] = {};
        #pragma unroll
        for (int ks = 0; ks < 8; ks++) mma16816(sc[ks & 3], a[ks][0], a[ks][1], a[ks][2], a[ks][3], kp[2 * ks], kp[2 * ks + 1]);
        __syncwarp();
        if (lane < 2) mbar_arrive(bempty + 8 * s);
        const float scale = 0.08838834764831845f, l2e = 1.4426950408889634f;
        uint32_t u0 = pack2((sc[0][0] + sc[1][0]) + (sc[2][0] + sc[3][0]), (sc[0][2] + sc[1][2]) + (sc[2][2] + sc[3][2]));
        uint32_t u1 = pack2((sc[0][1] + sc[1][1]) + (sc[2][1] + sc[3][1]), (sc[0][3] + sc[1][3]) + (sc[2][3] + sc[3][3]));
        u0 = pack2(bf_lo(u0) * scale, bf_hi(u0) * scale);
        u1 = pack2(bf_lo(u1) * scale, bf_hi(u1) * scale);
        uint32_t mx = max2(u0, u1);
        {
            const uint32_t a1 = __shfl_xor_sync(~0u, mx, 1), a2 = __shfl_xor_sync(~0u, mx, 2), a3 = __shfl_xor_sync(~0u, mx, 3);
            mx = max2(max2(mx, a1), max2(a2, a3));
        }
        const float e0 = ex2((bf_lo(u0) - bf_lo(mx)) * l2e), e1 = ex2((bf_lo(u1) - bf_lo(mx)) * l2e);
        const float e2 = ex2((bf_hi(u0) - bf_hi(mx)) * l2e), e3 = ex2((bf_hi(u1) - bf_hi(mx)) * l2e);
        float s0 = e0 + e1, s1 = e2 + e3;
        {
            const float a1 = __shfl_xor_sync(~0u, s0, 1), b1 = __shfl_xor_sync(~0u, s1, 1);
            const float a2 = __shfl_xor_sync(~0u, s0, 2), b2 = __shfl_xor_sync(~0u, s1, 2);
            const float a3 = __shfl_xor_sync(~0u, s0, 3), b3 = __shfl_xor_sync(~0u, s1, 3);
            s0 = (s0 + a1) + (a2 + a3); s1 = (s1 + b1) + (b2 + b3);
        }
        const float r0 = rcpa(s0), r1 = rcpa(s1);
        const uint32_t pa0 = pack2(e0 * r0, e1 * r0), pa1 = pack2(e2 * r1, e3 * r1);
        if (first) {
            mbar_wait_cluster(bfrag + 16 * hg + 8);
            #pragma unroll
            for (int i = 0; i < 4; i++)
                ldsm4(sfrag + hg * 4096 + 2048 + i * 512 + (li >> 1) * 128 + (((2 * mi + (li & 1)) ^ (li & 6)) << 4), vp[4 * i], vp[4 * i + 1], vp[4 * i + 2], vp[4 * i + 3]);
        }
        #pragma unroll
        for (int H = 0; H < 2; H++) {
            uint4 lo[2], hi[2];
            #pragma unroll
            for (int J = 0; J < 2; J++) {
                float c[4][4];
                #pragma unroll
                for (int u = 0; u < 4; u++) mma1688z(c[u], pa0, pa1, vp[H * 8 + J * 4 + u]);
                lo[J] = make_uint4(pack2(c[0][0], c[0][1]), pack2(c[1][0], c[1][1]), pack2(c[2][0], c[2][1]), pack2(c[3][0], c[3][1]));
                hi[J] = make_uint4(pack2(c[0][2], c[0][3]), pack2(c[1][2], c[1][3]), pack2(c[2][2], c[2][3]), pack2(c[3][2], c[3][3]));
            }
            const bool od = g & 1;
            const uint4 xl = shfl_xor4(od ? lo[0] : lo[1], 4), xh = shfl_xor4(od ? hi[0] : hi[1], 4);
            bf16* pe = orow + H * 64;
            stg4(pe, od ? xl : lo[0]);
            stg4(pe + 2 * DH, od ? lo[1] : xl);
            stg4(pe + 8 * DH, od ? xh : hi[0]);
            stg4(pe + 10 * DH, od ? hi[1] : xh);
        }
    }
}

typedef CUresult (*EncodeFn)(CUtensorMap*, CUtensorMapDataType, cuuint32_t, void*, const cuuint64_t*, const cuuint64_t*,
                             const cuuint32_t*, const cuuint32_t*, CUtensorMapInterleave, CUtensorMapSwizzle,
                             CUtensorMapL2promotion, CUtensorMapFloatOOBfill);

void make_map(EncodeFn enc, CUtensorMap* m, void* p, int d0, int row_bytes, int stride2, int d3, int stride3, int b2, int b3) {
    cuuint32_t es[4] = {1, 1, 1, 1};
    cuuint64_t d[4] = {(cuuint64_t)d0, 8, 2, (cuuint64_t)d3};
    cuuint64_t s[3] = {(cuuint64_t)row_bytes, (cuuint64_t)stride2, (cuuint64_t)stride3};
    cuuint32_t b[4] = {64, 8, (cuuint32_t)b2, (cuuint32_t)b3};
    enc(m, CU_TENSOR_MAP_DATA_TYPE_BFLOAT16, 4, p, d, s, b, es, CU_TENSOR_MAP_INTERLEAVE_NONE, CU_TENSOR_MAP_SWIZZLE_128B,
        CU_TENSOR_MAP_L2_PROMOTION_L2_128B, CU_TENSOR_MAP_FLOAT_OOB_FILL_NONE);
}

void launch(void* const* d_in, void* d_out, const Pace& s0, const Pace& s1) {
    void* fn = nullptr;
    cudaDriverEntryPointQueryResult qr;
    cudaGetDriverEntryPoint("cuTensorMapEncodeTiled", &fn, cudaEnableDefault, &qr);
    EncodeFn enc = (EncodeFn)fn;
    CUtensorMap mq, mk, mv, me, mf;
    make_map(enc, &mq, d_in[0], 64, 256, 128, 8192, 2048, 2, 4);
    make_map(enc, &mk, d_in[1], 64, 256, 128, 8192, 2048, 1, 8);
    make_map(enc, &mv, d_in[2], 64, 256, 128, 8192, 2048, 1, 8);
    make_map(enc, &me, d_in[3], 768, 4096, 2048, 2, 512, 2, 2);
    make_map(enc, &mf, d_in[4], 768, 4096, 512, 2, 2048, 2, 2);
    Params pp;
    pp.k = (const char*)d_in[1];
    pp.e = (const char*)d_in[3];
    pp.f = (const char*)d_in[4];
    pp.out = (bf16*)d_out;
    pp.c[0] = s0; pp.c[1] = s1;
    cudaFuncSetAttribute(linformer_kernel, cudaFuncAttributeMaxDynamicSharedMemorySize, SMEM_BYTES);
    cudaFuncSetAttribute(linformer_kernel, cudaFuncAttributeNonPortableClusterSizeAllowed, 1);
    cudaLaunchConfig_t cfg = {};
    cfg.gridDim = dim3(128);
    cfg.blockDim = dim3(NTHR);
    cfg.dynamicSmemBytes = SMEM_BYTES;
    cfg.stream = cudaStreamPerThread;
    cudaLaunchAttribute at[2];
    at[0].id = cudaLaunchAttributeClusterDimension;
    at[0].val.clusterDim.x = 16; at[0].val.clusterDim.y = 1; at[0].val.clusterDim.z = 1;
    at[1].id = cudaLaunchAttributeClusterSchedulingPolicyPreference;
    at[1].val.clusterSchedulingPolicyPreference = cudaClusterSchedulingPolicyLoadBalancing;
    cfg.attrs = at; cfg.numAttrs = 2;
    cudaLaunchKernelEx(&cfg, linformer_kernel, pp, mk, mv, me, mf, mq);
}

}

extern "C" void kernel_launch(void* const* d_in, const int* in_sizes, int n_in, void* d_out, int out_size) {
    (void)in_sizes; (void)n_in; (void)out_size;
    lf::launch(d_in, d_out, {720, 329, 380, 335}, {880, 302, 360, 400});
}
```
